```python
import torch

def _softmax(x, axis=-1):
    return torch.softmax(x, dim=axis)
def _gelu(x):
    return torch.nn.functional.gelu(x, approximate="tanh")
def _silu(x):
    return torch.nn.functional.silu(x)
def _sigmoid(x):
    return torch.sigmoid(x)
def _layernorm(x, axis=-1, eps=1e-5):
    m = x.mean(dim=axis, keepdim=True)
    v = x.var(dim=axis, keepdim=True, unbiased=False)
    return (x - m) / torch.sqrt(v + eps)
def _scatter_add(tgt, idx, src, axis=0):
    return tgt.clone().index_add_(axis, idx, src)
def _segment_sum(src, seg, n):
    out = torch.zeros((n,) + src.shape[1:], dtype=src.dtype)
    return out.index_add_(0, seg, src)
def _pad(x, pw):
    flat = tuple(v for pair in reversed(pw) for v in pair)
    return torch.nn.functional.pad(x, flat)

kernel_name = 'standalone__modern_conv_block_replknet__vision'

def setup_inputs():

    _w = (lambda a: (lambda t: t.to(torch.bfloat16) if t.is_floating_point() else t)(torch.as_tensor(a)))
    H = W = 512
    C = 96
    K = 3
    return {
        "x": _w((lambda *s: torch.randn(*s, dtype=torch.bfloat16) * 0.05)(1, H, W, C)),
        "dw_large": _w((lambda *s: torch.randn(*s, dtype=torch.bfloat16) * 0.4)(K, K, C) * (1.0 / K)),
        "dw_small": _w((lambda *s: torch.randn(*s, dtype=torch.bfloat16) * 0.4)(5, 5, C) * 0.2),
        "w1": _w((lambda *s: torch.randn(*s, dtype=torch.bfloat16) * 0.4)(C, 4 * C) * (C ** -0.5)),
        "w2": _w((lambda *s: torch.randn(*s, dtype=torch.bfloat16) * 0.1)(4 * C, C) * ((4 * C) ** -0.5)),
    }

def reference(x, dw_large, dw_small, w1, w2):
    B, H, W, C = x.shape
    Kl = dw_large.shape[0]
    pl = (Kl - 1) // 2
    xpl = _pad(x, ((0,0),(pl,pl),(pl,pl),(0,0)))
    out = torch.zeros_like(x)
    for i in range(Kl):
        for j in range(Kl):
            out = out + xpl[:, i:i+H, j:j+W, :] * dw_large[i, j][None, None, None, :]
    Ks = dw_small.shape[0]
    ps = (Ks - 1) // 2
    xps = _pad(x, ((0,0),(ps,ps),(ps,ps),(0,0)))
    for i in range(Ks):
        for j in range(Ks):
            out = out + xps[:, i:i+H, j:j+W, :] * dw_small[i, j][None, None, None, :]
    h = _layernorm(out, axis=-1)
    h = _gelu(torch.einsum('bhwc,ce->bhwe', h, w1))
    h = torch.einsum('bhwe,ec->bhwc', h, w2)
    return x + h
```

```cpp
#include <cuda_runtime.h>
#include <cuda_bf16.h>
#include <cuda.h>
#include <stdint.h>
#include <type_traits>

#define TR_(i)
#define TRS_(i)
#define MLP_REGS 176
#define CONV_REGS 136

namespace {

constexpr int IMG_H = 512, IMG_W = 512, CH = 96, HID = 384;
constexpr int BW = 16;
constexpr int TR = 4;
constexpr int PXB = CH * 2;
constexpr int ROW_PX = BW + 4;
constexpr int ROW_BYTES = ROW_PX * PXB;
constexpr int UNIT_BYTES = TR * ROW_BYTES;
constexpr int NBANDS = IMG_W / BW;
constexpr int TPB = IMG_H / TR;
constexpr int NUM_TILES = NBANDS * TPB;
constexpr int STG_PITCH = 208;
constexpr int STG_BYTES = 64 * STG_PITCH;
constexpr int RES_BYTES = 64 * PXB;
constexpr int NTHREADS = 512;

constexpr int W1_BYTES = CH * HID * 2;
constexpr int W2_BYTES = HID * CH * 2;
constexpr int WPIECE = 12288;
constexpr int SM_W1 = 0;
constexpr int SM_W2 = SM_W1 + W1_BYTES;
constexpr int SM_RING = SM_W2 + W2_BYTES;
constexpr int SM_RES = SM_RING + 2 * UNIT_BYTES;
constexpr int SM_STG = SM_RES + 2 * RES_BYTES;
constexpr int SM_BAR = SM_STG + 2 * STG_BYTES;
constexpr int SMEM_TOTAL = SM_BAR + 256;
static_assert(SMEM_TOTAL <= 232448, "smem");

constexpr int B_RING_FULL = 0;
constexpr int B_RING_EMPTY = 2;
constexpr int B_STG_FULL = 4;
constexpr int B_STG_EMPTY = 6;
constexpr int B_RES_FULL = 8;
constexpr int B_OUT_READY = 10;
constexpr int B_WEIGHTS = 12;

constexpr int NB_WEIGHTS = 1;

constexpr int W1_LBO = 8 * HID * 2, W1_SBO = 128;
constexpr int W2_KG = 8 * CH * 2;
constexpr int W2_LBO = 8 * W2_KG, W2_SBO = 128;

constexpr float GELU_S = 0.3292034911525734f;
constexpr float GELU_C = 1.5188174288475842f;
constexpr uint32_t GELU_A2 = 0x40D940D9u;

__device__ __forceinline__ uint32_t smem_u32(const void* p) {
    return (uint32_t)__cvta_generic_to_shared(p);
}
__device__ __forceinline__ uint64_t make_desc(uint32_t addr, uint32_t lbo, uint32_t sbo) {
    return (uint64_t)((addr & 0x3FFFF) >> 4) | ((uint64_t)(lbo >> 4) << 16) | ((uint64_t)(sbo >> 4) << 32);
}
__device__ __forceinline__ void mbar_init(uint32_t bar, uint32_t cnt) {
    asm volatile("mbarrier.init.shared::cta.b64 [%0], %1;" ::"r"(bar), "r"(cnt));
}
__device__ __forceinline__ void mbar_expect_tx(uint32_t bar, uint32_t bytes) {
    asm volatile("mbarrier.arrive.expect_tx.shared::cta.b64 _, [%0], %1;" ::"r"(bar), "r"(bytes) : "memory");
}
__device__ __forceinline__ void mbar_arrive_if(uint32_t bar, bool pred) {
    asm volatile("{\n.reg .pred p;\nsetp.ne.u32 p, %1, 0;\n@p mbarrier.arrive.shared::cta.b64 _, [%0];\n}\n"
                 ::"r"(bar), "r"((uint32_t)pred) : "memory");
}
__device__ __forceinline__ void mbar_wait(uint32_t bar, uint32_t parity) {
    asm volatile(
        "{\n"
        ".reg .pred p;\n"
        "WAIT_LOOP:\n"
        "mbarrier.try_wait.parity.shared::cta.b64 p, [%0], %1, %2;\n"
        "@p bra WAIT_DONE;\n"
        "bra WAIT_LOOP;\n"
        "WAIT_DONE:\n"
        "}\n" ::"r"(bar), "r"(parity), "r"(20000) : "memory");
}
__device__ __forceinline__ void tma_load3d(uint32_t dst, const CUtensorMap* map, int cx, int cy, uint32_t bar) {
    asm volatile(
        "cp.async.bulk.tensor.3d.shared::cluster.global.mbarrier::complete_tx::bytes [%0], [%1, {%2, %3, %4}], [%5];"
        ::"r"(dst), "l"((uint64_t)map), "r"(0), "r"(cx), "r"(cy), "r"(bar) : "memory");
}
__device__ __forceinline__ void nb_sync(int id, int cnt) {
    asm volatile("bar.sync %0, %1;" ::"r"(id), "r"(cnt) : "memory");
}
__device__ __forceinline__ uint4 lds128(uint32_t addr) {
    uint4 v;
    asm volatile("ld.shared.v4.u32 {%0,%1,%2,%3}, [%4];" : "=r"(v.x), "=r"(v.y), "=r"(v.z), "=r"(v.w) : "r"(addr));
    return v;
}
__device__ __forceinline__ void lds64(uint32_t& a, uint32_t& b, uint32_t addr) {
    asm volatile("ld.shared.v2.u32 {%0,%1}, [%2];" : "=r"(a), "=r"(b) : "r"(addr));
}
__device__ __forceinline__ void lds32(uint32_t& a, uint32_t addr) {
    asm volatile("ld.shared.u32 %0, [%1];" : "=r"(a) : "r"(addr));
}
__device__ __forceinline__ void sts128(uint32_t addr, uint4 v) {
    asm volatile("st.shared.v4.u32 [%0], {%1,%2,%3,%4};" ::"r"(addr), "r"(v.x), "r"(v.y), "r"(v.z), "r"(v.w) : "memory");
}
__device__ __forceinline__ void sts64(uint32_t addr, uint32_t a, uint32_t b) {
    asm volatile("st.shared.v2.u32 [%0], {%1,%2};" ::"r"(addr), "r"(a), "r"(b) : "memory");
}
__device__ __forceinline__ void sts32(uint32_t addr, uint32_t a) {
    asm volatile("st.shared.u32 [%0], %1;" ::"r"(addr), "r"(a) : "memory");
}
__device__ __forceinline__ uint32_t hfma2(uint32_t a, uint32_t b, uint32_t c) {
    uint32_t d;
    asm("fma.rn.bf16x2 %0, %1, %2, %3;" : "=r"(d) : "r"(a), "r"(b), "r"(c));
    return d;
}
__device__ __forceinline__ uint32_t hmul2(uint32_t a, uint32_t b) {
    uint32_t d;
    asm("mul.rn.bf16x2 %0, %1, %2;" : "=r"(d) : "r"(a), "r"(b));
    return d;
}
__device__ __forceinline__ uint32_t hadd2(uint32_t a, uint32_t b) {
    uint32_t d;
    asm("add.rn.bf16x2 %0, %1, %2;" : "=r"(d) : "r"(a), "r"(b));
    return d;
}
__device__ __forceinline__ float bf_lo(uint32_t v) { return __uint_as_float(v << 16); }
__device__ __forceinline__ float bf_hi(uint32_t v) { return __uint_as_float(v & 0xffff0000u); }
__device__ __forceinline__ uint32_t pack_bf16(float lo, float hi) {
    uint32_t d;
    asm("cvt.rn.bf16x2.f32 %0, %1, %2;" : "=r"(d) : "f"(hi), "f"(lo));
    return d;
}
__device__ __forceinline__ uint32_t pack_f16(float lo, float hi) {
    uint32_t d;
    asm("cvt.rn.f16x2.f32 %0, %1, %2;" : "=r"(d) : "f"(hi), "f"(lo));
    return d;
}
__device__ __forceinline__ uint32_t bf2h(uint32_t v, float sc) { return pack_f16(bf_lo(v) * sc, bf_hi(v) * sc); }
__device__ __forceinline__ uint4 bf2h4(uint4 v, float sc) {
    return make_uint4(bf2h(v.x, sc), bf2h(v.y, sc), bf2h(v.z, sc), bf2h(v.w, sc));
}
__device__ __forceinline__ uint32_t gelu2(uint32_t y) {
    uint32_t t, u, th, r;
    asm("fma.rn.f16x2 %0, %1, %1, %2;" : "=r"(t) : "r"(y), "r"(GELU_A2));
    asm("mul.rn.f16x2 %0, %1, %2;" : "=r"(u) : "r"(y), "r"(t));
    asm("tanh.approx.f16x2 %0, %1;" : "=r"(th) : "r"(u));
    asm("fma.rn.f16x2 %0, %1, %2, %1;" : "=r"(r) : "r"(y), "r"(th));
    return r;
}
__device__ __forceinline__ uint32_t resadd(uint32_t h, uint32_t x) {
    float lo, hi;
    asm("{\n.reg .b16 l, h;\nmov.b32 {l, h}, %2;\ncvt.f32.f16 %0, l;\ncvt.f32.f16 %1, h;\n}\n" : "=f"(lo), "=f"(hi) : "r"(h));
    return hadd2(pack_bf16(lo, hi), x);
}

#define WG_FENCE() asm volatile("wgmma.fence.sync.aligned;" ::: "memory")
#define WG_COMMIT() asm volatile("wgmma.commit_group.sync.aligned;" ::: "memory")
#define WG_WAIT(n) asm volatile("wgmma.wait_group.sync.aligned " #n ";" ::: "memory")

__device__ __forceinline__ void wgmma_rs(uint32_t (&d)[24], uint32_t a0, uint32_t a1, uint32_t a2, uint32_t a3,
                                           uint64_t desc) {
    asm volatile(
        "{\n"
        ".reg .pred p;\n"
        "setp.ne.b32 p, 1, 0;\n"
        "wgmma.mma_async.sync.aligned.m64n96k16.f16.f16.f16 {"
        "%0,%1,%2,%3,%4,%5,%6,%7,%8,%9,%10,%11,%12,%13,%14,%15,"
        "%16,%17,%18,%19,%20,%21,%22,%23"
        "}, {%24,%25,%26,%27}, %28, p, 1, 1, 1;\n"
        "}\n"
        : "+r"(d[0]), "+r"(d[1]), "+r"(d[2]), "+r"(d[3]), "+r"(d[4]), "+r"(d[5]), "+r"(d[6]), "+r"(d[7]),
          "+r"(d[8]), "+r"(d[9]), "+r"(d[10]), "+r"(d[11]), "+r"(d[12]), "+r"(d[13]), "+r"(d[14]), "+r"(d[15]),
          "+r"(d[16]), "+r"(d[17]), "+r"(d[18]), "+r"(d[19]), "+r"(d[20]), "+r"(d[21]), "+r"(d[22]), "+r"(d[23])
        : "r"(a0), "r"(a1), "r"(a2), "r"(a3), "l"(desc));
}
__device__ __forceinline__ void wgmma_rs_t(uint32_t (&d)[24], uint32_t a0, uint32_t a1, uint32_t a2, uint32_t a3,
                                           uint64_t desc) {
    asm volatile(
        "{\n"
        ".reg .pred p;\n"
        "setp.ne.b32 p, 0, 0;\n"
        "wgmma.mma_async.sync.aligned.m64n96k16.f16.f16.f16 {"
        "%0,%1,%2,%3,%4,%5,%6,%7,%8,%9,%10,%11,%12,%13,%14,%15,"
        "%16,%17,%18,%19,%20,%21,%22,%23"
        "}, {%24,%25,%26,%27}, %28, p, 1, 1, 1;\n"
        "}\n"
        : "+r"(d[0]), "+r"(d[1]), "+r"(d[2]), "+r"(d[3]), "+r"(d[4]), "+r"(d[5]), "+r"(d[6]), "+r"(d[7]),
          "+r"(d[8]), "+r"(d[9]), "+r"(d[10]), "+r"(d[11]), "+r"(d[12]), "+r"(d[13]), "+r"(d[14]), "+r"(d[15]),
          "+r"(d[16]), "+r"(d[17]), "+r"(d[18]), "+r"(d[19]), "+r"(d[20]), "+r"(d[21]), "+r"(d[22]), "+r"(d[23])
        : "r"(a0), "r"(a1), "r"(a2), "r"(a3), "l"(desc));
}
__device__ __forceinline__ void wgmma_rs_z(uint32_t (&d)[24], uint32_t a0, uint32_t a1, uint32_t a2, uint32_t a3,
                                           uint64_t desc) {
    asm volatile(
        "{\n"
        ".reg .pred p;\n"
        "setp.ne.b32 p, 0, 0;\n"
        "wgmma.mma_async.sync.aligned.m64n96k16.f16.f16.f16 {"
        "%0,%1,%2,%3,%4,%5,%6,%7,%8,%9,%10,%11,%12,%13,%14,%15,"
        "%16,%17,%18,%19,%20,%21,%22,%23"
        "}, {%24,%25,%26,%27}, %28, p, 1, 1, 1;\n"
        "}\n"
        : "=r"(d[0]), "=r"(d[1]), "=r"(d[2]), "=r"(d[3]), "=r"(d[4]), "=r"(d[5]), "=r"(d[6]), "=r"(d[7]),
          "=r"(d[8]), "=r"(d[9]), "=r"(d[10]), "=r"(d[11]), "=r"(d[12]), "=r"(d[13]), "=r"(d[14]), "=r"(d[15]),
          "=r"(d[16]), "=r"(d[17]), "=r"(d[18]), "=r"(d[19]), "=r"(d[20]), "=r"(d[21]), "=r"(d[22]), "=r"(d[23])
        : "r"(a0), "r"(a1), "r"(a2), "r"(a3), "l"(desc));
}

__device__ __forceinline__ void ldsm4(uint32_t& a, uint32_t& b, uint32_t& c, uint32_t& d, uint32_t addr) {
    asm volatile("ldmatrix.sync.aligned.m8n8.x4.shared.b16 {%0,%1,%2,%3}, [%4];"
                 : "=r"(a), "=r"(b), "=r"(c), "=r"(d) : "r"(addr));
}
__device__ __forceinline__ void ldsm2(uint32_t& a, uint32_t& b, uint32_t addr) {
    asm volatile("ldmatrix.sync.aligned.m8n8.x2.shared.b16 {%0,%1}, [%2];" : "=r"(a), "=r"(b) : "r"(addr));
}
__device__ __forceinline__ void ldsm1(uint32_t& a, uint32_t addr) {
    asm volatile("ldmatrix.sync.aligned.m8n8.x1.shared.b16 {%0}, [%1];" : "=r"(a) : "r"(addr));
}
__device__ __forceinline__ void stsm4(uint32_t addr, uint32_t a, uint32_t b, uint32_t c, uint32_t d) {
    asm volatile("stmatrix.sync.aligned.m8n8.x4.shared.b16 [%0], {%1,%2,%3,%4};"
                 ::"r"(addr), "r"(a), "r"(b), "r"(c), "r"(d) : "memory");
}
__device__ __forceinline__ void stsm2(uint32_t addr, uint32_t a, uint32_t b) {
    asm volatile("stmatrix.sync.aligned.m8n8.x2.shared.b16 [%0], {%1,%2};" ::"r"(addr), "r"(a), "r"(b) : "memory");
}
__device__ __forceinline__ uint32_t after(uint32_t addr, uint32_t v, uint32_t zero) {
    uint32_t d;
    asm("lop3.b32 %0, %1, %2, %3, 0xEA;" : "=r"(d) : "r"(v), "r"(zero), "r"(addr));
    return d;
}
__device__ __forceinline__ uint32_t ldg32(const uint32_t* p) {
    uint32_t v;
    asm volatile("ld.global.nc.u32 %0, [%1];" : "=r"(v) : "l"(p));
    return v;
}
__device__ __forceinline__ void tma_prefetch3d(const CUtensorMap* map, int cx, int cy) {
    asm volatile("cp.async.bulk.prefetch.tensor.3d.L2.global [%0, {%1, %2, %3}];"
                 ::"l"((uint64_t)map), "r"(0), "r"(cx), "r"(cy) : "memory");
}
#define SCHED_FENCE() asm volatile("pmevent.mask 0;" ::: "memory")

template <int B, int E, typename F>
__device__ __forceinline__ void static_for(F&& f) {
    if constexpr (B < E) {
        f(std::integral_constant<int, B>{});
        static_for<B + 1, E>(f);
    }
}
template <int N>
__device__ __forceinline__ void wg_wait() {
    asm volatile("wgmma.wait_group.sync.aligned %0;" ::"n"(N) : "memory");
}
__device__ __forceinline__ void gemm1_step(uint32_t (&h)[24], const uint32_t (&a)[6][4], uint64_t w1desc, int c, int ks) {
    const uint64_t d = w1desc + (uint64_t)((c * 12 * W1_SBO + ks * 2 * W1_LBO) >> 4);
    if (ks == 0) wgmma_rs_t(h, a[0][0], a[0][1], a[0][2], a[0][3], d);
    else wgmma_rs(h, a[ks][0], a[ks][1], a[ks][2], a[ks][3], d);
}
__device__ __forceinline__ void gemm2_step(uint32_t (&acc2)[24], const uint32_t (&p)[4], uint64_t w2desc, int j) {
    const uint64_t d = w2desc + (uint64_t)(((16 * (j % 3) + j / 3) * W2_KG) >> 4);
    if (j == 0) wgmma_rs_t(acc2, p[0], p[1], p[2], p[3], d);
    else wgmma_rs(acc2, p[0], p[1], p[2], p[3], d);
}
__device__ __forceinline__ uint32_t gelu_front(uint32_t y) {
    uint32_t t, u;
    asm("fma.rn.f16x2 %0, %1, %1, %2;" : "=r"(t) : "r"(y), "r"(GELU_A2));
    asm("mul.rn.f16x2 %0, %1, %2;" : "=r"(u) : "r"(y), "r"(t));
    return u;
}
__device__ __forceinline__ void gelu_tanh(uint16_t& lo, uint16_t& hi, uint32_t u) {
    asm("{\n.reg .b16 l, h;\nmov.b32 {l, h}, %2;\ntanh.approx.f16 %0, l;\ntanh.approx.f16 %1, h;\n}\n"
        : "=h"(lo), "=h"(hi) : "r"(u));
}
__device__ __forceinline__ uint32_t gelu_back(uint32_t y, uint16_t lo, uint16_t hi) {
    uint32_t g;
    asm("{\n.reg .b32 t;\nmov.b32 t, {%2, %3};\nfma.rn.f16x2 %0, %1, t, %1;\n}\n" : "=r"(g) : "r"(y), "h"(lo), "h"(hi));
    return g;
}

template <int NP, int S, int NX>
__device__ __forceinline__ void conv_row(uint32_t (&o)[NP], uint32_t (&acc)[4][NP], const uint32_t (&w)[25],
                                         const uint32_t (&x)[NX]) {
    uint32_t t[5][NP];
#define EXP_DX 5
#pragma unroll
    for (int dx = 0; dx < EXP_DX; dx++) {
#pragma unroll
        for (int i = 0; i < NP; i++) {
#pragma unroll
            for (int r = 0; r < 5; r++) {
                const uint32_t xv = x[i * S + dx], wv = w[(4 - r) * 5 + dx];
                if (dx > 0) t[r][i] = hfma2(xv, wv, t[r][i]);
                else if (r < 4) t[r][i] = hfma2(xv, wv, acc[r][i]);
                else t[r][i] = hmul2(xv, wv);
            }
        }
    }
#pragma unroll
    for (int i = 0; i < NP; i++) {
        o[i] = t[0][i];
#pragma unroll
        for (int r = 0; r < 4; r++) acc[r][i] = t[r + 1][i];
    }
}

__global__ void __launch_bounds__(NTHREADS, 1)
fused_block_kernel(const __grid_constant__ CUtensorMap rowmap, const __grid_constant__ CUtensorMap tilemap,
                   const __grid_constant__ CUtensorMap outmap,
                   const __nv_bfloat16* __restrict__ dwl, const __nv_bfloat16* __restrict__ dws,
                   const __nv_bfloat16* __restrict__ w1, const __nv_bfloat16* __restrict__ w2,
                   int tq, int trem) {
    extern __shared__ __align__(1024) uint8_t smem[];
    const uint32_t sbase = smem_u32(smem);
    const int tid = threadIdx.x;
    const int wid = __shfl_sync(0xffffffffu, tid >> 5, 0);
    const int wg = wid >> 2, warp = wid & 3;
    const int wtid = tid & 127;
    const int lane = tid & 31;
    const uint32_t bars = sbase + SM_BAR;

    if (tid == NTHREADS - 32) {
        const int pf = blockIdx.x % 72;
        asm volatile("cp.async.bulk.prefetch.L2.global [%0], %1;"
                     ::"l"(reinterpret_cast<const char*>(pf < 36 ? (const void*)w1 : (const void*)w2) + (pf % 36) * 2048),
                     "r"(2048) : "memory");
#pragma unroll 1
        for (int i = 0; i < 12; i++) {
            const uint32_t wb = bars + 8 * (B_WEIGHTS + i);
            mbar_init(wb, 1);
            asm volatile("fence.mbarrier_init.release.cluster;" ::: "memory");
            mbar_expect_tx(wb, WPIECE);
            const char* src = reinterpret_cast<const char*>(i < 6 ? (const void*)w1 : (const void*)w2) + (i < 6 ? i : i - 6) * WPIECE;
            asm volatile("cp.async.bulk.shared::cluster.global.mbarrier::complete_tx::bytes [%0], [%1], %2, [%3];"
                         ::"r"(sbase + i * WPIECE), "l"(src), "r"(WPIECE), "r"(wb) : "memory");
        }
    }
    const int t0 = (int)blockIdx.x * tq + min((int)blockIdx.x, trem);
    const int nt = tq + ((int)blockIdx.x < trem ? 1 : 0);
    const int t1 = t0 + nt;
    const int G0 = min(nt, TPB - t0 % TPB) + 1;
    const int G = G0 <= nt ? nt + 2 : G0;

    if (wg == 3) {
        const bool leader = lane == 0;
        const int x0 = (t0 / TPB) * BW - 2, y0 = (t0 % TPB) * TR - 2;
        auto issue_unit = [&](int j) {
            const uint32_t fb = bars + 8 * (B_RING_FULL + (j & 1));
            mbar_expect_tx(fb, UNIT_BYTES);
            tma_load3d(sbase + SM_RING + (j & 1) * UNIT_BYTES, &rowmap, j < G0 ? x0 : x0 + BW,
                       j < G0 ? y0 + TR * j : TR * (j - G0) - 2, fb);
        };
        auto prefetch_unit = [&](int j) {
            if (j < G) tma_prefetch3d(&rowmap, j < G0 ? x0 : x0 + BW, j < G0 ? y0 + TR * j : TR * (j - G0) - 2);
        };
        if (leader) {
            if (warp == 0) {
                mbar_init(bars + 8 * B_RING_FULL, 1);
                mbar_init(bars + 8 * B_RING_FULL + 8, 1);
                mbar_init(bars + 8 * B_RING_EMPTY, 4);
                mbar_init(bars + 8 * B_RING_EMPTY + 8, 4);
                asm volatile("fence.mbarrier_init.release.cluster;" ::: "memory");
#pragma unroll 1
                for (int j = 0; j < 2; j++) issue_unit(j);
            } else if (warp < 3) {
                mbar_init(bars + 8 * (B_RES_FULL + warp - 1), 1);
                mbar_init(bars + 8 * (B_OUT_READY + warp - 1), 4);
                mbar_init(bars + 8 * (B_STG_FULL + warp - 1), 4);
                mbar_init(bars + 8 * (B_STG_EMPTY + warp - 1), 4);
                asm volatile("fence.mbarrier_init.release.cluster;" ::: "memory");
            }
        }
        __syncthreads();
        asm volatile("setmaxnreg.dec.sync.aligned.u32 24;");
        if (leader) {
            if (warp == 0) {
#define PFD 2
                mbar_wait(bars + 8 * (B_RING_FULL + 1), 0);
#pragma unroll 1
                for (int j = 2; j < 2 + PFD; j++) prefetch_unit(j);
#pragma unroll 1
                for (int j = 2; j < G; j++) {
                    mbar_wait(bars + 8 * (B_RING_EMPTY + (j & 1)), ((j >> 1) & 1) ^ 1);
                    issue_unit(j);
                    prefetch_unit(j + PFD);
                }
            } else if (warp < 3) {
                const int m = warp - 1;
                const uint32_t fb = bars + 8 * (B_RES_FULL + m), buf = sbase + SM_RES + m * RES_BYTES;
#pragma unroll 1
                for (int T = t0 + m - 2, i = 0; T < t1; T += 2, i++) {
                    mbar_wait(bars + 8 * (B_OUT_READY + m), i & 1);
                    if (i >= 1) {
                        asm volatile("cp.async.bulk.tensor.3d.global.shared::cta.bulk_group [%0, {%1, %2, %3}], [%4];"
                                     ::"l"((uint64_t)&outmap), "r"(0), "r"((T / TPB) * BW), "r"((T % TPB) * TR), "r"(buf)
                                     : "memory");
                        asm volatile("cp.async.bulk.commit_group;" ::: "memory");
                        asm volatile("cp.async.bulk.wait_group.read 0;" ::: "memory");
                    }
                    const int Tn = T + 2;
                    if (Tn < t1) {
                        mbar_expect_tx(fb, RES_BYTES);
                        tma_load3d(buf, &tilemap, (Tn / TPB) * BW, (Tn % TPB) * TR, fb);
                    }
                }
                asm volatile("cp.async.bulk.wait_group 0;" ::: "memory");
            }
        }
    } else if (wg == 2) {
        const int cb = 32 + (lane & 15);
        const uint32_t* ps = reinterpret_cast<const uint32_t*>(dws);
        const uint32_t* pl = reinterpret_cast<const uint32_t*>(dwl);
        uint32_t wa[25], wb[25];
#pragma unroll
        for (int tap = 0; tap < 25; tap++) {
            wa[tap] = ldg32(ps + tap * (CH / 2) + lane);
            wb[tap] = ldg32(ps + tap * (CH / 2) + cb);
        }
        uint32_t la[9], lb[9];
#pragma unroll
        for (int i = 0; i < 9; i++) {
            la[i] = ldg32(pl + i * (CH / 2) + lane);
            lb[i] = ldg32(pl + i * (CH / 2) + cb);
        }
        SCHED_FENCE();
        __syncthreads();
        asm volatile("setmaxnreg.inc.sync.aligned.u32 %0;" :: "n"(CONV_REGS));
        SCHED_FENCE();
#pragma unroll
        for (int i = 0; i < 9; i++) {
            const int tap = (i / 3 + 1) * 5 + (i % 3 + 1);
            wa[tap] = hadd2(wa[tap], la[i]);
            wb[tap] = hadd2(wb[tap], lb[i]);
        }
        uint32_t acca[4][4], accb[4][2];
#pragma unroll
        for (int r = 0; r < 4; r++) acca[r][0] = acca[r][1] = acca[r][2] = acca[r][3] = accb[r][0] = accb[r][1] = 0u;
        const int mi = lane >> 3, mr = lane & 7;
        const uint32_t ring_a = sbase + SM_RING + (4 * warp + mi) * PXB + mr * 16;
        const uint32_t ring_b = sbase + SM_RING + (4 * warp + mi + (mr >> 2)) * PXB + 128 + (mr & 3) * 16;
        const uint32_t stg_a = sbase + SM_STG + (4 * warp + mi) * STG_PITCH + mr * 16;
        const uint32_t stg_b = sbase + SM_STG + (4 * warp + 2 * (mi & 1) + (mr >> 2)) * STG_PITCH + 128 + (mr & 3) * 16;
        TRS_(0);
        uint32_t xa[2][8], xb[2][7];
        auto fetch_a = [&](int buf, uint32_t off) {
            ldsm4(xa[buf][0], xa[buf][1], xa[buf][2], xa[buf][3], ring_a + off);
            ldsm4(xa[buf][4], xa[buf][5], xa[buf][6], xa[buf][7], ring_a + off + 4 * PXB);
        };
        auto fetch_b = [&](int buf, uint32_t off) {
            ldsm4(xb[buf][0], xb[buf][1], xb[buf][2], xb[buf][3], ring_b + off);
            ldsm2(xb[buf][4], xb[buf][5], ring_b + off + 4 * PXB);
            ldsm1(xb[buf][6], ring_b + off + 6 * PXB);
        };
        mbar_wait(bars + 8 * B_RING_FULL, 0);
        TRS_(1);
        fetch_a(0, 0);
        fetch_b(0, 0);
        fetch_a(1, ROW_BYTES);
        int k = 0;
#pragma unroll 1
        for (int gi = 0; gi < G; gi++) {
            const uint32_t cur = (gi & 1) * UNIT_BYTES, nxt = cur ^ UNIT_BYTES;
            const uint32_t dst = (k & 1) * STG_BYTES;
#pragma unroll
            for (int R = 0; R < 4; R++) {
                uint32_t oa[4], ob[2];
                conv_row<4, 1>(oa, acca, wa, xa[R & 1]);
                fetch_b((R + 1) & 1, R < 3 ? cur + (R + 1) * ROW_BYTES : nxt);
                if (R == 0) mbar_wait(bars + 8 * (B_STG_EMPTY + (k & 1)), ((k >> 1) & 1) ^ 1);
                if (R == 2 && gi + 1 < G) mbar_wait(bars + 8 * (B_RING_FULL + ((gi + 1) & 1)), ((gi + 1) >> 1) & 1);
                SCHED_FENCE();
                stsm4(stg_a + dst + R * (BW * STG_PITCH), oa[0], oa[1], oa[2], oa[3]);
                conv_row<2, 2>(ob, accb, wb, xb[R & 1]);
                fetch_a(R & 1, R < 2 ? cur + (R + 2) * ROW_BYTES : nxt + (R - 2) * ROW_BYTES);
                stsm2(stg_b + dst + R * (BW * STG_PITCH), ob[0], ob[1]);
                if (R < 3) SCHED_FENCE();
            }
            const bool real = (gi != 0) && (gi != G0);
            if (gi < 4) TRS_(5 + gi);
            __syncwarp();
            mbar_arrive_if(bars + 8 * (B_RING_EMPTY + (gi & 1)), lane == 0);
            mbar_arrive_if(bars + 8 * (B_STG_FULL + (k & 1)), real && lane == 0);
            k += real ? 1 : 0;
        }
        TRS_(4);
    } else {
        __syncthreads();
        asm volatile("setmaxnreg.inc.sync.aligned.u32 %0;" :: "n"(MLP_REGS));
        const int ntw = (nt - wg + 1) >> 1;
        TRS_(0);
        const int g = lane >> 2, q = lane & 3;
        const uint64_t w1desc = make_desc(sbase + SM_W1, W1_LBO, W1_SBO);
        const uint64_t w2desc = make_desc(sbase + SM_W2, W2_LBO, W2_SBO);
        const uint32_t ldm_addr = sbase + SM_STG + wg * STG_BYTES +
                                  (16 * warp + (lane & 7) + ((lane >> 3) & 1) * 8) * STG_PITCH + (lane >> 4) * 16;
        const uint32_t res_addr = sbase + SM_RES + wg * RES_BYTES + (16 * warp + g) * PXB + q * 16;

        uint32_t a[6][4], r[6][4];
        uint32_t h[2][24], acc2[24];
        uint32_t p[24][4], u[2][4];
        uint16_t tl[2][4], tg[2][4];
        uint4 xr[6];
        uint32_t ps[2][2], rp[2], cp[2];
        float mean[2], var[2];
        auto fence_regs = [&](auto& v) {
#pragma unroll
            for (int i = 0; i < (int)(sizeof(v) / 4); i++) asm volatile("" : "+r"(v[i]) :: "memory");
        };
#pragma unroll
        for (int i = 0; i < 24; i++) acc2[i] = h[0][i] = h[1][i] = 0u;
#pragma unroll
        for (int i = 0; i < 6; i++) xr[i] = make_uint4(0, 0, 0, 0);
        fence_regs(acc2);
        fence_regs(h[0]);
        fence_regs(h[1]);
#define WD 3

        auto layernorm = [&](auto Tc) {
            constexpr int t = decltype(Tc)::value;
                if constexpr (t == 10 || t == 11) {
                    constexpr int k0 = 3 * (t - 10);
#pragma unroll
                    for (int j = 0; j < 2; j++)
                        ps[t - 10][j] = hadd2(hadd2(hadd2(r[k0][j], r[k0][j + 2]), hadd2(r[k0 + 1][j], r[k0 + 1][j + 2])),
                                              hadd2(r[k0 + 2][j], r[k0 + 2][j + 2]));
                }
                if constexpr (t == 11) {
#pragma unroll
                    for (int j = 0; j < 2; j++) {
                        const uint32_t s2 = hadd2(ps[0][j], ps[1][j]);
                        mean[j] = bf_lo(s2) + bf_hi(s2);
                        var[j] = __shfl_xor_sync(0xffffffffu, mean[j], 1);
                    }
                }
                if constexpr (t == 12) {
#pragma unroll
                    for (int j = 0; j < 2; j++) {
                        mean[j] += var[j];
                        var[j] = __shfl_xor_sync(0xffffffffu, mean[j], 2);
                    }
                }
                if constexpr (t == 13) {
#pragma unroll
                    for (int j = 0; j < 2; j++) {
                        const float nm = (mean[j] + var[j]) * (-1.0f / CH);
                        cp[j] = pack_bf16(nm, nm);
                        mean[j] = nm - bf_lo(cp[j]);
                    }
                }
                if constexpr (t == 13 || t == 14) {
                    constexpr int k0 = 3 * (t - 13);
#pragma unroll
                    for (int j = 0; j < 4; j++) {
#pragma unroll
                        for (int ks = k0; ks < k0 + 3; ks++) r[ks][j] = hadd2(r[ks][j], cp[j & 1]);
                    }
#pragma unroll
                    for (int j = 0; j < 2; j++) {
                        const uint32_t q0 = hfma2(r[k0 + 2][j], r[k0 + 2][j],
                                                  hfma2(r[k0 + 1][j], r[k0 + 1][j], hmul2(r[k0][j], r[k0][j])));
                        const uint32_t q1 = hfma2(r[k0 + 2][j + 2], r[k0 + 2][j + 2],
                                                  hfma2(r[k0 + 1][j + 2], r[k0 + 1][j + 2], hmul2(r[k0][j + 2], r[k0][j + 2])));
                        ps[t - 13][j] = hadd2(q0, q1);
                    }
                }
                if constexpr (t == 14) {
#pragma unroll
                    for (int j = 0; j < 2; j++) {
                        const uint32_t s2 = hadd2(ps[0][j], ps[1][j]);
                        var[j] = bf_lo(s2) + bf_hi(s2);
                        ps[0][j] = __shfl_xor_sync(0xffffffffu, __float_as_uint(var[j]), 1);
                    }
                }
                if constexpr (t == 15) {
#pragma unroll
                    for (int j = 0; j < 2; j++) {
                        var[j] += __uint_as_float(ps[0][j]);
                        ps[0][j] = __shfl_xor_sync(0xffffffffu, __float_as_uint(var[j]), 2);
                    }
                }
                if constexpr (t == 16) {
#pragma unroll
                    for (int j = 0; j < 2; j++) {
                        const float vr = fmaxf(fmaf(-mean[j], mean[j], (var[j] + __uint_as_float(ps[0][j])) * (1.0f / CH)), 0.f);
                        const float rs = rsqrtf(vr + 1e-5f) * GELU_S;
                        rp[j] = pack_bf16(rs, rs);
                        cp[j] = pack_bf16(mean[j] * rs, mean[j] * rs);
                    }
                }
                if constexpr (t >= 17 && t <= 19) {
#pragma unroll
                    for (int ks = 2 * (t - 17); ks < 2 * (t - 17) + 2; ks++) {
#pragma unroll
                        for (int j = 0; j < 4; j++) {
                            const uint32_t n = hfma2(r[ks][j], rp[j & 1], cp[j & 1]);
                            a[ks][j] = pack_f16(bf_lo(n), bf_hi(n));
                        }
                    }
                }
        };
        auto gelu = [&](auto Tc) {
            constexpr int t = decltype(Tc)::value;
            constexpr int sf = (t + 1) % 24, sb = (t + 23) % 24;
            if constexpr (t >= 0) {
#pragma unroll
                for (int i = 0; i < 4; i++) gelu_tanh(tl[t & 1][i], tg[t & 1][i], u[t & 1][i]);
            }
#pragma unroll
            for (int i = 0; i < 4; i++) u[(t + 1) & 1][i] = gelu_front(h[(sf / 6) & 1][4 * (sf % 6) + i]);
            if constexpr (t >= 1) {
#pragma unroll
                for (int i = 0; i < 4; i++)
                    p[sb][i] = gelu_back(h[(sb / 6) & 1][4 * (sb % 6) + i], tl[(t + 1) & 1][i], tg[(t + 1) & 1][i]);
            }
        };
        auto release_stg = [&](bool pred) {
            __syncwarp();
            mbar_arrive_if(bars + 8 * (B_STG_EMPTY + wg), pred && lane == 0);
        };
        auto out_ready = [&]() {
            asm volatile("fence.proxy.async.shared::cta;" ::: "memory");
            __syncwarp();
            mbar_arrive_if(bars + 8 * (B_OUT_READY + wg), lane == 0);
        };
#pragma unroll 1
#define PASS0 1
        for (int pass = PASS0; pass < 2; pass++) {
            if (pass) {
                TRS_(5);
        {
            const int kk = lane & 7, a0 = (kk + (lane >> 3)) & 7;
#pragma unroll 1
            for (int t = wid; t < 24; t += 8) {
                const uint32_t base = sbase + SM_W1 + (t >> 1) * W1_LBO + (t & 1) * 384;
                uint4 v[6];
                mbar_wait(bars + 8 * (B_WEIGHTS + (t >> 2)), 0);
                TRS_(6 + (t >> 3));
#pragma unroll
                for (int i = 0; i < 6; i++) v[i] = lds128(base + (i >> 1) * 128 + kk * (HID * 2) + (a0 ^ ((i & 1) * 4)) * 16);
                __syncwarp();
#pragma unroll
                for (int i = 0; i < 6; i++)
                    sts128(base + (i >> 1) * 128 + (a0 ^ ((i & 1) * 4)) * (HID * 2) + kk * 16, bf2h4(v[i], 1.0f));
            }
            TRS_(1);
            const int q2 = lane & 3, k2 = lane >> 2;
#pragma unroll 1
            for (int t = wid; t < 48; t += 8) {
                const uint32_t base = sbase + SM_W2 + t * W2_KG;
                uint4 v[3];
                mbar_wait(bars + 8 * (B_WEIGHTS + 6 + (t >> 3)), 0);
#pragma unroll
                for (int i = 0; i < 3; i++) v[i] = lds128(base + k2 * (CH * 2) + i * 64 + q2 * 16);
                __syncwarp();
#pragma unroll
                for (int i = 0; i < 3; i++) {
                    const uint32_t d = base + i * 512 + k2 * 16 + q2 * 4;
                    const uint4 c = bf2h4(v[i], GELU_C);
                    sts32(d, c.x);
                    sts32(d + 128, c.y);
                    sts32(d + 256, c.z);
                    sts32(d + 384, c.w);
                }
            }
        }
        asm volatile("fence.proxy.async.shared::cta;" ::: "memory");
        nb_sync(NB_WEIGHTS, 256);
        TRS_(2);

                mbar_wait(bars + 8 * (B_STG_FULL + wg), 0);
                TRS_(3);
            }
#pragma unroll
            for (int ks = 0; ks < 6; ks++) ldsm4(r[ks][0], r[ks][1], r[ks][2], r[ks][3], ldm_addr + ks * 32);
            static_for<10, 20>(layernorm);
            SCHED_FENCE();
            release_stg(pass);
            WG_FENCE();
#pragma unroll
            for (int ks = 0; ks < 6; ks++) gemm1_step(h[0], a, w1desc, 0, ks);
            WG_COMMIT();
            wg_wait<0>();
            fence_regs(h[0]);
            static_for<-1, 3>(gelu);
        }
#pragma unroll 1
        for (int it = 0;; it++) {
            bool done = false;
            static_for<3, 27>([&](auto Tc) {
                constexpr int t = decltype(Tc)::value;
                if (done) return;
                if constexpr (t == 3) {
                    wg_wait<0>();
                    fence_regs(acc2);
                    fence_regs(h[0]);
                }
                if constexpr (t == 5) wg_wait<0>();
                else if constexpr (t % 6 == 5) wg_wait<2>();
                else if constexpr (t > 6 + WD) wg_wait<WD>();
                if constexpr (t % 6 == 5) fence_regs(h[((t + 1) / 6) & 1]);
                if constexpr (t == 9) out_ready();
                if constexpr (t == 6) {
                    if (it == ntw) { done = true; return; }
                    if (it + 1 < ntw) mbar_wait(bars + 8 * (B_STG_FULL + wg), (it + 1) & 1);
                }
                if constexpr (t == 21) {
                    mbar_wait(bars + 8 * (B_RES_FULL + wg), it & 1);
                }
                if constexpr (t == 3 || (t >= 6 && t <= 25)) {
                    WG_FENCE();
                    if constexpr (t == 3) {
#pragma unroll
                        for (int ks = 0; ks < 6; ks++) gemm1_step(h[1], a, w1desc, 1, ks);
                    }
                    if constexpr (t >= 7 && (t % 6 == 1 || t % 6 == 2) && t < 24) {
                        constexpr int c = (t / 6 + 1) % 4;
#pragma unroll
                        for (int ks = 0; ks < 3; ks++) gemm1_step(h[c & 1], a, w1desc, c, (t % 6 - 1) * 3 + ks);
                    }
                    if constexpr (t == 6) {
#pragma unroll
                        for (int j = 0; j < 4; j++) gemm2_step(acc2, p[j], w2desc, j);
                    }
                    if constexpr (t >= 6) gemm2_step(acc2, p[t - 2], w2desc, t - 2);
                    WG_COMMIT();
                }
                if constexpr (t >= 6 && t <= 8) {
#pragma unroll
                    for (int ks = 2 * (t - 6); ks < 2 * (t - 6) + 2; ks++)
                        ldsm4(r[ks][0], r[ks][1], r[ks][2], r[ks][3], ldm_addr + ks * 32);
                }
                if constexpr (t >= 21) xr[t - 21] = lds128(res_addr + ((t - 21) / 3) * 8 * PXB + ((t - 21) % 3) * 64);
                if constexpr (t == 12) release_stg(true);
                gelu(Tc);
                if constexpr (t <= 5) {
#pragma unroll
                    for (int i = 2 * (t - 3); i < 2 * (t - 3) + 2; i++) {
                        const int half = i / 3, j = i % 3;
                        uint4 o;
                        o.x = resadd(acc2[8 * j + 0 + half], xr[i].x);
                        o.y = resadd(acc2[8 * j + 2 + half], xr[i].y);
                        o.z = resadd(acc2[8 * j + 4 + half], xr[i].z);
                        o.w = resadd(acc2[8 * j + 6 + half], xr[i].w);
                        sts128(res_addr + half * 8 * PXB + j * 64, o);
                    }
                }
                layernorm(Tc);
                SCHED_FENCE();
            });
            if (done) break;
            wg_wait<0>();
        }
        out_ready();
        TRS_(4);
    }
}

typedef CUresult (*PFN_encodeTiled)(CUtensorMap*, CUtensorMapDataType, cuuint32_t, void*, const cuuint64_t*,
                                    const cuuint64_t*, const cuuint32_t*, const cuuint32_t*, CUtensorMapInterleave,
                                    CUtensorMapSwizzle, CUtensorMapL2promotion, CUtensorMapFloatOOBfill);

}

extern "C" void kernel_launch(void* const* d_in, const int* in_sizes, int n_in, void* d_out, int out_size) {
    const __nv_bfloat16* x = (const __nv_bfloat16*)d_in[0];
    const __nv_bfloat16* dwl = (const __nv_bfloat16*)d_in[1];
    const __nv_bfloat16* dws = (const __nv_bfloat16*)d_in[2];
    const __nv_bfloat16* w1 = (const __nv_bfloat16*)d_in[3];
    const __nv_bfloat16* w2 = (const __nv_bfloat16*)d_in[4];
    __nv_bfloat16* out = (__nv_bfloat16*)d_out;

    static PFN_encodeTiled encode = nullptr;
    static int num_sms = 0;
    if (!encode) {
        void* fn = nullptr;
        cudaDriverEntryPointQueryResult qres;
        cudaGetDriverEntryPoint("cuTensorMapEncodeTiled", &fn, cudaEnableDefault, &qres);
        encode = (PFN_encodeTiled)fn;
        cudaFuncSetAttribute(fused_block_kernel, cudaFuncAttributeMaxDynamicSharedMemorySize, SMEM_TOTAL);
        cudaDeviceGetAttribute(&num_sms, cudaDevAttrMultiProcessorCount, 0);
    }
    CUtensorMap rowmap, tilemap, outmap;
    cuuint64_t gdim[3] = {(cuuint64_t)CH, (cuuint64_t)IMG_W, (cuuint64_t)IMG_H};
    cuuint64_t gstride[2] = {(cuuint64_t)PXB, (cuuint64_t)IMG_W * PXB};
    cuuint32_t estr[3] = {1, 1, 1};
    cuuint32_t box_row[3] = {(cuuint32_t)CH, (cuuint32_t)ROW_PX, (cuuint32_t)TR};
    cuuint32_t box_tile[3] = {(cuuint32_t)CH, (cuuint32_t)BW, (cuuint32_t)TR};
    encode(&rowmap, CU_TENSOR_MAP_DATA_TYPE_BFLOAT16, 3, (void*)x, gdim, gstride, box_row, estr,
           CU_TENSOR_MAP_INTERLEAVE_NONE, CU_TENSOR_MAP_SWIZZLE_NONE, CU_TENSOR_MAP_L2_PROMOTION_L2_256B,
           CU_TENSOR_MAP_FLOAT_OOB_FILL_NONE);
    encode(&tilemap, CU_TENSOR_MAP_DATA_TYPE_BFLOAT16, 3, (void*)x, gdim, gstride, box_tile, estr,
           CU_TENSOR_MAP_INTERLEAVE_NONE, CU_TENSOR_MAP_SWIZZLE_NONE, CU_TENSOR_MAP_L2_PROMOTION_L2_256B,
           CU_TENSOR_MAP_FLOAT_OOB_FILL_NONE);
    encode(&outmap, CU_TENSOR_MAP_DATA_TYPE_BFLOAT16, 3, (void*)out, gdim, gstride, box_tile, estr,
           CU_TENSOR_MAP_INTERLEAVE_NONE, CU_TENSOR_MAP_SWIZZLE_NONE, CU_TENSOR_MAP_L2_PROMOTION_NONE,
           CU_TENSOR_MAP_FLOAT_OOB_FILL_NONE);
    const int grid = num_sms >= 32 ? (num_sms < NUM_TILES / 2 ? num_sms : NUM_TILES / 2) : 32;
    fused_block_kernel<<<grid, NTHREADS, SMEM_TOTAL>>>(rowmap, tilemap, outmap, dwl, dws, w1, w2, NUM_TILES / grid,
                                                        NUM_TILES % grid);
}
```

```cpp
#include <cuda_runtime.h>
#include <cuda_bf16.h>
#include <cuda.h>
#include <stdint.h>
#include <type_traits>

#define TRS_(i)
#define PTR_(k)

namespace {

constexpr int IMG_H = 512, IMG_W = 512, CH = 96, HID = 384;
constexpr int BW = 16;
constexpr int TR = 4;
constexpr int NT = 32;
constexpr int NCTA = (IMG_W / BW) * (IMG_H / (TR * NT));
constexpr int PXB = CH * 2;
constexpr int ROW_PX = BW + 4;
constexpr int ROW_BYTES = ROW_PX * PXB;
constexpr int UNIT_BYTES = TR * ROW_BYTES;
constexpr int STG_PITCH = 208;
constexpr int STG_BYTES = 64 * STG_PITCH;
constexpr int OUT_BYTES = 64 * PXB;
constexpr int NTHREADS = 512;
constexpr int MLP_REGS = 168, CONV_REGS = 152, TMA_REGS = 24;

constexpr int W1_BYTES = CH * HID * 2;
constexpr int W2_BYTES = HID * CH * 2;
constexpr int WPIECE = 24576;
constexpr int SM_W1 = 0;
constexpr int SM_W2 = SM_W1 + W1_BYTES;
constexpr int SM_RING = SM_W2 + W2_BYTES;
constexpr int SM_OUT = SM_RING + 2 * UNIT_BYTES;
constexpr int SM_STG = SM_OUT + 2 * OUT_BYTES;
constexpr int SM_BAR = SM_STG + 2 * STG_BYTES;
constexpr int SMEM_TOTAL = SM_BAR + 256;
static_assert(SMEM_TOTAL <= 232448, "smem");

constexpr int B_RING_FULL = 0;
constexpr int B_RING_EMPTY = 2;
constexpr int B_STG_FULL = 4;
constexpr int B_STG_EMPTY = 6;
constexpr int B_X_FULL = 8;
constexpr int B_OUT_READY = 10;
constexpr int B_OUT_FREE = 12;
constexpr int B_FILTER = 14;
constexpr int B_WEIGHTS = 16;

constexpr int W1_LBO = 8 * HID * 2, W1_SBO = 128;
constexpr int W2_KG = 8 * CH * 2;
constexpr int W2_LBO = 8 * W2_KG, W2_SBO = 128;

constexpr float GELU_S = 0.3292034911525734f;
constexpr float GELU_C = 1.5188174288475842f;
constexpr uint32_t GELU_A2 = 0x40D940D9u;

__device__ __forceinline__ uint32_t smem_u32(const void* p) {
    return (uint32_t)__cvta_generic_to_shared(p);
}
__device__ __forceinline__ uint64_t make_desc(uint32_t addr, uint32_t lbo, uint32_t sbo) {
    return (uint64_t)((addr & 0x3FFFF) >> 4) | ((uint64_t)(lbo >> 4) << 16) | ((uint64_t)(sbo >> 4) << 32);
}
__device__ __forceinline__ void mbar_init(uint32_t bar, uint32_t cnt) {
    asm volatile("mbarrier.init.shared::cta.b64 [%0], %1;" ::"r"(bar), "r"(cnt));
}
__device__ __forceinline__ void mbar_expect_tx(uint32_t bar, uint32_t bytes) {
    asm volatile("mbarrier.arrive.expect_tx.shared::cta.b64 _, [%0], %1;" ::"r"(bar), "r"(bytes) : "memory");
}
__device__ __forceinline__ void mbar_arrive_if(uint32_t bar, bool pred) {
    asm volatile("{\n.reg .pred p;\nsetp.ne.u32 p, %1, 0;\n@p mbarrier.arrive.shared::cta.b64 _, [%0];\n}\n"
                 ::"r"(bar), "r"((uint32_t)pred) : "memory");
}
__device__ __forceinline__ void mbar_wait(uint32_t bar, uint32_t parity) {
    asm volatile(
        "{\n"
        ".reg .pred p;\n"
        "WAIT_LOOP:\n"
        "mbarrier.try_wait.parity.shared::cta.b64 p, [%0], %1, %2;\n"
        "@p bra WAIT_DONE;\n"
        "bra WAIT_LOOP;\n"
        "WAIT_DONE:\n"
        "}\n" ::"r"(bar), "r"(parity), "r"(20000) : "memory");
}
__device__ __forceinline__ void tma_load3d(uint32_t dst, const CUtensorMap* map, int cx, int cy, uint32_t bar) {
    asm volatile(
        "cp.async.bulk.tensor.3d.shared::cluster.global.mbarrier::complete_tx::bytes [%0], [%1, {%2, %3, %4}], [%5];"
        ::"r"(dst), "l"((uint64_t)map), "r"(0), "r"(cx), "r"(cy), "r"(bar) : "memory");
}
__device__ __forceinline__ void tma_prefetch3d(const CUtensorMap* map, int cx, int cy) {
    asm volatile("cp.async.bulk.prefetch.tensor.3d.L2.global [%0, {%1, %2, %3}];"
                 ::"l"((uint64_t)map), "r"(0), "r"(cx), "r"(cy) : "memory");
}
__device__ __forceinline__ void bulk_load(uint32_t dst, const void* src, uint32_t bytes, uint32_t bar) {
    asm volatile("cp.async.bulk.shared::cluster.global.mbarrier::complete_tx::bytes [%0], [%1], %2, [%3];"
                 ::"r"(dst), "l"(src), "r"(bytes), "r"(bar) : "memory");
}
__device__ __forceinline__ uint4 lds128(uint32_t addr) {
    uint4 v;
    asm volatile("ld.shared.v4.u32 {%0,%1,%2,%3}, [%4];" : "=r"(v.x), "=r"(v.y), "=r"(v.z), "=r"(v.w) : "r"(addr));
    return v;
}
__device__ __forceinline__ uint32_t lds32(uint32_t addr) {
    uint32_t v;
    asm volatile("ld.shared.u32 %0, [%1];" : "=r"(v) : "r"(addr));
    return v;
}
__device__ __forceinline__ void sts128(uint32_t addr, uint4 v) {
    asm volatile("st.shared.v4.u32 [%0], {%1,%2,%3,%4};" ::"r"(addr), "r"(v.x), "r"(v.y), "r"(v.z), "r"(v.w) : "memory");
}
__device__ __forceinline__ void sts32(uint32_t addr, uint32_t a) {
    asm volatile("st.shared.u32 [%0], %1;" ::"r"(addr), "r"(a) : "memory");
}
__device__ __forceinline__ void ldsm4(uint32_t& a, uint32_t& b, uint32_t& c, uint32_t& d, uint32_t addr) {
    asm volatile("ldmatrix.sync.aligned.m8n8.x4.shared.b16 {%0,%1,%2,%3}, [%4];"
                 : "=r"(a), "=r"(b), "=r"(c), "=r"(d) : "r"(addr));
}
__device__ __forceinline__ void ldsm2(uint32_t& a, uint32_t& b, uint32_t addr) {
    asm volatile("ldmatrix.sync.aligned.m8n8.x2.shared.b16 {%0,%1}, [%2];" : "=r"(a), "=r"(b) : "r"(addr));
}
__device__ __forceinline__ void stsm4(uint32_t addr, uint32_t a, uint32_t b, uint32_t c, uint32_t d) {
    asm volatile("stmatrix.sync.aligned.m8n8.x4.shared.b16 [%0], {%1,%2,%3,%4};"
                 ::"r"(addr), "r"(a), "r"(b), "r"(c), "r"(d) : "memory");
}
__device__ __forceinline__ void stsm2(uint32_t addr, uint32_t a, uint32_t b) {
    asm volatile("stmatrix.sync.aligned.m8n8.x2.shared.b16 [%0], {%1,%2};" ::"r"(addr), "r"(a), "r"(b) : "memory");
}
__device__ __forceinline__ uint32_t hfma2(uint32_t a, uint32_t b, uint32_t c) {
    uint32_t d;
    asm("fma.rn.bf16x2 %0, %1, %2, %3;" : "=r"(d) : "r"(a), "r"(b), "r"(c));
    return d;
}
__device__ __forceinline__ uint32_t hmul2(uint32_t a, uint32_t b) {
    uint32_t d;
    asm("mul.rn.bf16x2 %0, %1, %2;" : "=r"(d) : "r"(a), "r"(b));
    return d;
}
__device__ __forceinline__ uint32_t hadd2(uint32_t a, uint32_t b) {
    uint32_t d;
    asm("add.rn.bf16x2 %0, %1, %2;" : "=r"(d) : "r"(a), "r"(b));
    return d;
}
__device__ __forceinline__ uint32_t hsub2(uint32_t a, uint32_t b) {
    uint32_t d;
    asm("sub.rn.bf16x2 %0, %1, %2;" : "=r"(d) : "r"(a), "r"(b));
    return d;
}
__device__ __forceinline__ float bf_lo(uint32_t v) { return __uint_as_float(v << 16); }
__device__ __forceinline__ float bf_hi(uint32_t v) { return __uint_as_float(v & 0xffff0000u); }
__device__ __forceinline__ uint32_t pack_bf16(float lo, float hi) {
    uint32_t d;
    asm("cvt.rn.bf16x2.f32 %0, %1, %2;" : "=r"(d) : "f"(hi), "f"(lo));
    return d;
}
__device__ __forceinline__ uint32_t pack_f16(float lo, float hi) {
    uint32_t d;
    asm("cvt.rn.f16x2.f32 %0, %1, %2;" : "=r"(d) : "f"(hi), "f"(lo));
    return d;
}
__device__ __forceinline__ uint32_t bf2h(uint32_t v, float sc) { return pack_f16(bf_lo(v) * sc, bf_hi(v) * sc); }
__device__ __forceinline__ uint4 bf2h4(uint4 v, float sc) {
    return make_uint4(bf2h(v.x, sc), bf2h(v.y, sc), bf2h(v.z, sc), bf2h(v.w, sc));
}
__device__ __forceinline__ uint32_t h2bf(uint32_t h) {
    float lo, hi;
    asm("{\n.reg .b16 l, h;\nmov.b32 {l, h}, %2;\ncvt.f32.f16 %0, l;\ncvt.f32.f16 %1, h;\n}\n" : "=f"(lo), "=f"(hi) : "r"(h));
    return pack_bf16(lo, hi);
}

#define WG_FENCE() asm volatile("wgmma.fence.sync.aligned;" ::: "memory")
#define WG_COMMIT() asm volatile("wgmma.commit_group.sync.aligned;" ::: "memory")
template <int N>
__device__ __forceinline__ void wg_wait() {
    asm volatile("wgmma.wait_group.sync.aligned %0;" ::"n"(N) : "memory");
}
#define SCHED_FENCE() asm volatile("pmevent.mask 0;" ::: "memory")

template <bool ACC>
__device__ __forceinline__ void wgmma_rs(uint32_t (&d)[24], const uint32_t (&a)[4], uint64_t desc) {
    asm volatile(
        "{\n"
        ".reg .pred p;\n"
        "setp.ne.b32 p, %29, 0;\n"
        "wgmma.mma_async.sync.aligned.m64n96k16.f16.f16.f16 {"
        "%0,%1,%2,%3,%4,%5,%6,%7,%8,%9,%10,%11,%12,%13,%14,%15,"
        "%16,%17,%18,%19,%20,%21,%22,%23"
        "}, {%24,%25,%26,%27}, %28, p, 1, 1, 1;\n"
        "}\n"
        : "+r"(d[0]), "+r"(d[1]), "+r"(d[2]), "+r"(d[3]), "+r"(d[4]), "+r"(d[5]), "+r"(d[6]), "+r"(d[7]),
          "+r"(d[8]), "+r"(d[9]), "+r"(d[10]), "+r"(d[11]), "+r"(d[12]), "+r"(d[13]), "+r"(d[14]), "+r"(d[15]),
          "+r"(d[16]), "+r"(d[17]), "+r"(d[18]), "+r"(d[19]), "+r"(d[20]), "+r"(d[21]), "+r"(d[22]), "+r"(d[23])
        : "r"(a[0]), "r"(a[1]), "r"(a[2]), "r"(a[3]), "l"(desc), "n"(ACC ? 1 : 0));
}
__device__ __forceinline__ void gemm1_step(uint32_t (&h)[24], const uint32_t (&a)[6][4], uint64_t w1desc, int c, int ks) {
    const uint64_t d = w1desc + (uint64_t)((c * 12 * W1_SBO + ks * 2 * W1_LBO) >> 4);
    if (ks == 0) wgmma_rs<false>(h, a[0], d);
    else wgmma_rs<true>(h, a[ks], d);
}
__device__ __forceinline__ void gemm2_step(uint32_t (&acc2)[24], const uint32_t (&p)[4], uint64_t w2desc, int j) {
    const uint64_t d = w2desc + (uint64_t)(((16 * (j % 3) + j / 3) * W2_KG) >> 4);
    if (j == 0) wgmma_rs<false>(acc2, p, d);
    else wgmma_rs<true>(acc2, p, d);
}
__device__ __forceinline__ uint32_t gelu_front(uint32_t y) {
    uint32_t t, u;
    asm("fma.rn.f16x2 %0, %1, %1, %2;" : "=r"(t) : "r"(y), "r"(GELU_A2));
    asm("mul.rn.f16x2 %0, %1, %2;" : "=r"(u) : "r"(y), "r"(t));
    return u;
}
__device__ __forceinline__ void gelu_tanh(uint16_t& lo, uint16_t& hi, uint32_t u) {
    asm("{\n.reg .b16 l, h;\nmov.b32 {l, h}, %2;\ntanh.approx.f16 %0, l;\ntanh.approx.f16 %1, h;\n}\n"
        : "=h"(lo), "=h"(hi) : "r"(u));
}
__device__ __forceinline__ uint32_t gelu_back(uint32_t y, uint16_t lo, uint16_t hi) {
    uint32_t g;
    asm("{\n.reg .b32 t;\nmov.b32 t, {%2, %3};\nfma.rn.f16x2 %0, %1, t, %1;\n}\n" : "=r"(g) : "r"(y), "h"(lo), "h"(hi));
    return g;
}

template <int B, int E, typename F>
__device__ __forceinline__ void static_for(F&& f) {
    if constexpr (B < E) {
        f(std::integral_constant<int, B>{});
        static_for<B + 1, E>(f);
    }
}

template <int NP, int R0>
__device__ __forceinline__ void conv_row(uint32_t (&o)[2 * NP], uint32_t (&acc)[4][NP][3], const uint32_t (&w)[5][7],
                                         const uint32_t (&x)[2 * NP + 4]) {
    uint32_t e[NP + 1], f[NP + 1], t[5][NP][3];
#pragma unroll
    for (int i = 0; i <= NP; i++) {
        e[i] = hsub2(x[2 * i], x[2 * i + 1]);
        f[i] = hsub2(x[2 * i + 2], x[2 * i + 1]);
    }
#pragma unroll
    for (int p = 0; p < NP; p++) {
#pragma unroll
        for (int r = R0; r < 5; r++) {
            const uint32_t(&h)[7] = w[4 - r];
            t[r][p][1] = r < 4 ? hfma2(x[2 * p + 1], h[3], acc[r & 3][p][1]) : hmul2(x[2 * p + 1], h[3]);
            t[r][p][0] = r < 4 ? hfma2(x[2 * p + 4], h[2], acc[r & 3][p][0]) : hmul2(x[2 * p + 4], h[2]);
            t[r][p][2] = r < 4 ? hfma2(x[2 * p + 5], h[2], acc[r & 3][p][2]) : hmul2(x[2 * p + 5], h[2]);
        }
#pragma unroll
        for (int r = R0; r < 5; r++) {
            const uint32_t(&h)[7] = w[4 - r];
            t[r][p][1] = hfma2(x[2 * p + 3], h[4], t[r][p][1]);
            t[r][p][0] = hfma2(e[p], h[0], t[r][p][0]);
            t[r][p][2] = hfma2(f[p], h[5], t[r][p][2]);
        }
#pragma unroll
        for (int r = R0; r < 5; r++) {
            const uint32_t(&h)[7] = w[4 - r];
            t[r][p][0] = hfma2(e[p + 1], h[1], t[r][p][0]);
            t[r][p][2] = hfma2(f[p + 1], h[6], t[r][p][2]);
        }
        if (R0 == 0) {
            o[2 * p] = hadd2(t[0][p][0], t[0][p][1]);
            o[2 * p + 1] = hadd2(t[0][p][1], t[0][p][2]);
        }
#pragma unroll
        for (int r = (R0 > 0 ? R0 : 1); r < 5; r++)
#pragma unroll
            for (int m = 0; m < 3; m++) acc[r - 1][p][m] = t[r][p][m];
    }
}

constexpr int SG_LD = 6, SG_SUM = 8, SG_SH2 = 9, SG_CEN = 10, SG_VAR = 13, SG_VA2 = 14, SG_RS = 15, SG_NRM = 16, SG_CVT = 17;

__global__ void __launch_bounds__(NTHREADS, 1)
fused_block_kernel(const __grid_constant__ CUtensorMap rowmap, const __grid_constant__ CUtensorMap tilemap,
                   const __grid_constant__ CUtensorMap outmap,
                   const __nv_bfloat16* __restrict__ dwl, const __nv_bfloat16* __restrict__ dws,
                   const __nv_bfloat16* __restrict__ w1, const __nv_bfloat16* __restrict__ w2) {
    extern __shared__ __align__(1024) uint8_t smem[];
    const uint32_t sbase = smem_u32(smem);
    const int tid = threadIdx.x;
    const int wid = __shfl_sync(0xffffffffu, tid >> 5, 0);
    const int wg = wid >> 2, warp = wid & 3;
    const int lane = tid & 31;
    const uint32_t bars = sbase + SM_BAR;
    const int x0 = (blockIdx.x >> 2) * BW, y0 = (blockIdx.x & 3) * (TR * NT);

    if (tid == NTHREADS - 128) {
        const char* wsrc[2] = {reinterpret_cast<const char*>(w1), reinterpret_cast<const char*>(w2)};
        asm volatile("cp.async.bulk.prefetch.L2.global [%0], %1;"
                     ::"l"(wsrc[blockIdx.x & 1] + (blockIdx.x >> 1) * (W1_BYTES / (NCTA / 2))), "r"(W1_BYTES / (NCTA / 2))
                     : "memory");
        mbar_init(bars + 8 * B_FILTER, 1);
        mbar_init(bars + 8 * B_RING_FULL, 1);
        mbar_init(bars + 8 * B_RING_FULL + 8, 1);
#pragma unroll
        for (int i = 0; i < 6; i++) mbar_init(bars + 8 * (B_WEIGHTS + i), 1);
        asm volatile("fence.mbarrier_init.release.cluster;" ::: "memory");
        mbar_expect_tx(bars + 8 * B_FILTER, 34 * PXB);
        bulk_load(sbase + SM_OUT, dws, 25 * PXB, bars + 8 * B_FILTER);
        bulk_load(sbase + SM_OUT + 25 * PXB, dwl, 9 * PXB, bars + 8 * B_FILTER);
#pragma unroll
        for (int i = 0; i < 6; i++) {
            if (i < 2) {
                mbar_expect_tx(bars + 8 * (B_RING_FULL + i), UNIT_BYTES);
                tma_load3d(sbase + SM_RING + i * UNIT_BYTES, &rowmap, x0 - 2, y0 - 2 + TR * i, bars + 8 * (B_RING_FULL + i));
            }
            mbar_expect_tx(bars + 8 * (B_WEIGHTS + i), WPIECE);
            bulk_load(sbase + i * WPIECE, wsrc[i / 3] + (i % 3) * WPIECE, WPIECE, bars + 8 * (B_WEIGHTS + i));
        }
    } else if (tid == NTHREADS - 96) {
#pragma unroll
        for (int m = 0; m < 2; m++) {
            mbar_init(bars + 8 * (B_RING_EMPTY + m), 4);
            mbar_init(bars + 8 * (B_STG_FULL + m), 4);
            mbar_init(bars + 8 * (B_STG_EMPTY + m), 4);
            mbar_init(bars + 8 * (B_X_FULL + m), 1);
            mbar_init(bars + 8 * (B_OUT_READY + m), 4);
            mbar_init(bars + 8 * (B_OUT_FREE + m), 1);
        }
        asm volatile("fence.mbarrier_init.release.cluster;" ::: "memory");
    }
    __syncthreads();

    if (wg == 3) {
        asm volatile("setmaxnreg.dec.sync.aligned.u32 %0;" ::"n"(TMA_REGS));
        const int m = warp >> 1;
        if (lane == 0) {
            if (warp == 0 || warp == 3) {
                const uint32_t fb = bars + 8 * (B_RING_FULL + m);
                mbar_wait(fb, 0);
                tma_prefetch3d(&rowmap, x0 - 2, y0 - 2 + TR * (m + 2));
#pragma unroll 1
                for (int j = m + 2; j <= NT; j += 2) {
                    mbar_wait(bars + 8 * (B_RING_EMPTY + m), ((j >> 1) & 1) ^ 1);
                    mbar_expect_tx(fb, UNIT_BYTES);
                    tma_load3d(sbase + SM_RING + m * UNIT_BYTES, &rowmap, x0 - 2, y0 - 2 + TR * j, fb);
                    if (j + 2 <= NT) tma_prefetch3d(&rowmap, x0 - 2, y0 - 2 + TR * (j + 2));
                }
            } else {
                const uint32_t fb = bars + 8 * (B_X_FULL + m), buf = sbase + SM_OUT + m * OUT_BYTES;
                mbar_wait(bars + 8 * (B_OUT_READY + m), 0);
#pragma unroll 1
                for (int i = 0; i < NT / 2; i++) {
                    const int cy = y0 + TR * (2 * i + m);
                    PTR_(0);
                    mbar_expect_tx(fb, OUT_BYTES);
                    tma_load3d(buf, &tilemap, x0, cy, fb);
                    mbar_wait(fb, i & 1);
                    PTR_(1);
                    asm volatile("cp.async.bulk.tensor.3d.global.shared::cta.bulk_group [%0, {%1, %2, %3}], [%4];"
                                 ::"l"((uint64_t)&outmap), "r"(0), "r"(x0), "r"(cy), "r"(buf) : "memory");
                    asm volatile("cp.async.bulk.commit_group;" ::: "memory");
                    asm volatile("cp.async.bulk.wait_group 0;" ::: "memory");
                    PTR_(2);
                    mbar_arrive_if(bars + 8 * (B_OUT_FREE + m), true);
                    mbar_wait(bars + 8 * (B_OUT_READY + m), (i & 1) ^ 1);
                    PTR_(3);
                    asm volatile("cp.reduce.async.bulk.tensor.3d.global.shared::cta.add.bulk_group [%0, {%1, %2, %3}], [%4];"
                                 ::"l"((uint64_t)&outmap), "r"(0), "r"(x0), "r"(cy), "r"(buf) : "memory");
                    asm volatile("cp.async.bulk.commit_group;" ::: "memory");
                    asm volatile("cp.async.bulk.wait_group 0;" ::: "memory");
                    PTR_(4);
                }
            }
        }
    } else if (wg == 2) {
        asm volatile("setmaxnreg.inc.sync.aligned.u32 %0;" ::"n"(CONV_REGS));
        uint32_t wa[5][7], wb[5][7];
        {
            const uint32_t pa = sbase + SM_OUT + 4 * lane, pb = sbase + SM_OUT + 4 * (32 + (lane & 15));
            const bool mir = lane >= 16;
            mbar_wait(bars + 8 * B_FILTER, 0);
#pragma unroll
            for (int r = 0; r < 5; r++) {
                uint32_t u[5], v[5];
#pragma unroll
                for (int c = 0; c < 5; c++) {
                    u[c] = lds32(pa + (5 * r + c) * PXB);
                    v[c] = lds32(pb + (5 * r + c) * PXB);
                    if (r >= 1 && r <= 3 && c >= 1 && c <= 3) {
                        u[c] = hadd2(u[c], lds32(pa + (25 + 3 * (r - 1) + c - 1) * PXB));
                        v[c] = hadd2(v[c], lds32(pb + (25 + 3 * (r - 1) + c - 1) * PXB));
                    }
                }
#pragma unroll
                for (int c = 0; c < 2; c++) {
                    const uint32_t lo = v[c], hi = v[4 - c];
                    v[c] = mir ? hi : lo;
                    v[4 - c] = mir ? lo : hi;
                }
                wa[r][0] = u[0]; wa[r][1] = u[2]; wa[r][2] = u[4]; wa[r][3] = hadd2(u[0], u[1]);
                wa[r][4] = hadd2(u[2], u[3]); wa[r][5] = u[1]; wa[r][6] = u[3];
                wb[r][0] = v[0]; wb[r][1] = v[2]; wb[r][2] = v[4]; wb[r][3] = hadd2(v[0], v[1]);
                wb[r][4] = hadd2(v[2], v[3]); wb[r][5] = v[1]; wb[r][6] = v[3];
            }
        }
        const int mi = lane >> 3, mr = lane & 7, up = mr >> 2;
        const uint32_t ring_a = sbase + SM_RING + (4 * warp + mi) * PXB + mr * 16;
        const uint32_t ring_b0 = sbase + SM_RING + (4 * warp + (up ? 7 - mi : mi)) * PXB + 128 + (mr & 3) * 16;
        const uint32_t ring_b1 = sbase + SM_RING + (4 * warp + (up ? 3 - mi : 4 + mi)) * PXB + 128 + (mr & 3) * 16;
        const uint32_t stg_a = sbase + SM_STG + (4 * warp + mi) * STG_PITCH + mr * 16;
        const uint32_t stg_b = sbase + SM_STG + (4 * warp + (up ? 3 - mi : mi)) * STG_PITCH + 128 + (mr & 3) * 16;
        uint32_t acca[4][2][3], accb[4][1][3], xa[8], xb[6], oa[4], ob[2];
        auto fetch_a = [&](uint32_t off) {
            ldsm4(xa[0], xa[1], xa[2], xa[3], ring_a + off);
            ldsm4(xa[4], xa[5], xa[6], xa[7], ring_a + off + 4 * PXB);
        };
        auto fetch_b = [&](uint32_t off) {
            ldsm4(xb[0], xb[1], xb[2], xb[3], ring_b0 + off);
            ldsm2(xb[4], xb[5], ring_b1 + off);
        };
        TRS_(0);
        mbar_wait(bars + 8 * B_RING_FULL, 0);
        TRS_(1);
        static_for<0, 4>([&](auto Rc) {
            constexpr int R = decltype(Rc)::value;
            fetch_a(R * ROW_BYTES);
            fetch_b(R * ROW_BYTES);
            conv_row<2, 4 - R>(oa, acca, wa, xa);
            conv_row<1, 4 - R>(ob, accb, wb, xb);
        });
        SCHED_FENCE();
        __syncwarp();
        mbar_arrive_if(bars + 8 * B_RING_EMPTY, lane == 0);
        mbar_wait(bars + 8 * (B_RING_FULL + 1), 0);
        fetch_a(UNIT_BYTES);
        fetch_b(UNIT_BYTES);
        TRS_(5);
#pragma unroll 1
        for (int k = 0; k < NT; k++) {
            const uint32_t s = k & 1, ph = (k >> 1) & 1;
            const uint32_t nxt = s * UNIT_BYTES, cur = nxt ^ UNIT_BYTES, dst = s * STG_BYTES;
#pragma unroll
            for (int R = 0; R < 4; R++) {
                conv_row<2, 0>(oa, acca, wa, xa);
                fetch_a(R < 3 ? cur + (R + 1) * ROW_BYTES : nxt);
                if (R == 0) mbar_wait(bars + 8 * B_STG_EMPTY + 8 * s, ph ^ 1);
                if (R == 2 && k + 1 < NT) mbar_wait(bars + 8 * B_RING_FULL + 8 * s, ph ^ 1);
                SCHED_FENCE();
                stsm4(stg_a + dst + R * (BW * STG_PITCH), oa[0], oa[1], oa[2], oa[3]);
                conv_row<1, 0>(ob, accb, wb, xb);
                fetch_b(R < 3 ? cur + (R + 1) * ROW_BYTES : nxt);
                stsm2(stg_b + dst + R * (BW * STG_PITCH), ob[0], ob[1]);
                if (R < 3) SCHED_FENCE();
            }
            __syncwarp();
            mbar_arrive_if(bars + 8 * B_RING_EMPTY + 8 * (s ^ 1), lane == 0);
            mbar_arrive_if(bars + 8 * B_STG_FULL + 8 * s, lane == 0);
        }
        TRS_(4);
    } else {
        asm volatile("setmaxnreg.inc.sync.aligned.u32 %0;" ::"n"(MLP_REGS));
        TRS_(0);
        {
            const int kk = lane & 7, a0 = (kk + (lane >> 3)) & 7;
#pragma unroll 1
            for (int t = wid; t < 24; t += 8) {
                const uint32_t base = sbase + SM_W1 + (t >> 1) * W1_LBO + (t & 1) * 384;
                uint4 v[6];
                mbar_wait(bars + 8 * (B_WEIGHTS + (t >> 3)), 0);
#pragma unroll
                for (int i = 0; i < 6; i++) v[i] = lds128(base + (i >> 1) * 128 + kk * (HID * 2) + (a0 ^ ((i & 1) * 4)) * 16);
                __syncwarp();
#pragma unroll
                for (int i = 0; i < 6; i++)
                    sts128(base + (i >> 1) * 128 + (a0 ^ ((i & 1) * 4)) * (HID * 2) + kk * 16, bf2h4(v[i], 1.0f));
            }
            TRS_(1);
            const int q2 = lane & 3, k2 = lane >> 2;
#pragma unroll 1
            for (int t = wid; t < 48; t += 8) {
                const uint32_t base = sbase + SM_W2 + t * W2_KG;
                uint4 v[3];
                mbar_wait(bars + 8 * (B_WEIGHTS + 3 + (t >> 4)), 0);
#pragma unroll
                for (int i = 0; i < 3; i++) v[i] = lds128(base + k2 * (CH * 2) + i * 64 + q2 * 16);
                __syncwarp();
#pragma unroll
                for (int i = 0; i < 3; i++) {
                    const uint32_t d = base + i * 512 + k2 * 16 + q2 * 4;
                    const uint4 c = bf2h4(v[i], GELU_C);
                    sts32(d, c.x);
                    sts32(d + 128, c.y);
                    sts32(d + 256, c.z);
                    sts32(d + 384, c.w);
                }
            }
            asm volatile("fence.proxy.async.shared::cta;" ::: "memory");
            asm volatile("bar.sync 1, 256;" ::: "memory");
            TRS_(2);
        }

        const uint64_t w1desc = make_desc(sbase + SM_W1, W1_LBO, W1_SBO);
        const uint64_t w2desc = make_desc(sbase + SM_W2, W2_LBO, W2_SBO);
        const uint32_t ldm_addr = sbase + SM_STG + wg * STG_BYTES +
                                  (16 * warp + (lane & 7) + ((lane >> 3) & 1) * 8) * STG_PITCH + (lane >> 4) * 16;
        const uint32_t out_addr = sbase + SM_OUT + wg * OUT_BYTES + (16 * warp + (lane >> 2)) * PXB + (lane & 3) * 16;

        uint32_t a[6][4], r[6][4];
        uint32_t h[2][24], acc2[24];
        uint32_t p[24][4], u[2][4];
        uint16_t tl[2][4], tg[2][4];
        uint32_t ps[2][2], sq[2][4], rp[2], cp[2];
        float mean[2], var[2];
        auto fence_regs = [&](auto& v) {
#pragma unroll
            for (int i = 0; i < (int)(sizeof(v) / 4); i++) asm volatile("" : "+r"(v[i]) :: "memory");
        };
#pragma unroll
        for (int i = 0; i < 24; i++) acc2[i] = h[0][i] = h[1][i] = 0u;
        fence_regs(acc2);
        fence_regs(h[0]);
        fence_regs(h[1]);

        auto layernorm = [&](auto Tc) {
            constexpr int t = decltype(Tc)::value;
            if constexpr (t == SG_LD || t == SG_LD + 1) {
#pragma unroll
                for (int ks = 3 * (t - SG_LD); ks < 3 * (t - SG_LD) + 3; ks++)
                    ldsm4(r[ks][0], r[ks][1], r[ks][2], r[ks][3], ldm_addr + ks * 32);
            }
            if constexpr (t == SG_SUM - 1 || t == SG_SUM) {
                constexpr int k0 = 3 * (t - SG_SUM + 1);
#pragma unroll
                for (int j = 0; j < 2; j++)
                    ps[t - SG_SUM + 1][j] = hadd2(hadd2(hadd2(r[k0][j], r[k0][j + 2]), hadd2(r[k0 + 1][j], r[k0 + 1][j + 2])),
                                                  hadd2(r[k0 + 2][j], r[k0 + 2][j + 2]));
            }
            if constexpr (t == SG_SUM) {
#pragma unroll
                for (int j = 0; j < 2; j++) {
                    const uint32_t s2 = hadd2(ps[0][j], ps[1][j]);
                    mean[j] = bf_lo(s2) + bf_hi(s2);
                    var[j] = __shfl_xor_sync(0xffffffffu, mean[j], 1);
                }
            }
            if constexpr (t == SG_SH2) {
#pragma unroll
                for (int j = 0; j < 2; j++) {
                    mean[j] += var[j];
                    var[j] = __shfl_xor_sync(0xffffffffu, mean[j], 2);
                }
            }
            if constexpr (t == SG_CEN) {
#pragma unroll
                for (int j = 0; j < 2; j++) {
                    const float nm = (mean[j] + var[j]) * (-1.0f / CH);
                    cp[j] = pack_bf16(nm, nm);
                    mean[j] = nm - bf_lo(cp[j]);
                }
            }
            if constexpr (t >= SG_CEN && t < SG_CEN + 3) {
#pragma unroll
                for (int ks = (t - SG_CEN) * 2; ks < (t - SG_CEN) * 2 + 2; ks++) {
#pragma unroll
                    for (int j = 0; j < 4; j++) {
                        r[ks][j] = hadd2(r[ks][j], cp[j & 1]);
                        sq[ks & 1][j] = ks < 2 ? hmul2(r[ks][j], r[ks][j]) : hfma2(r[ks][j], r[ks][j], sq[ks & 1][j]);
                    }
                }
            }
            if constexpr (t == SG_VAR) {
#pragma unroll
                for (int j = 0; j < 2; j++) {
                    const uint32_t s2 = hadd2(hadd2(sq[0][j], sq[1][j]), hadd2(sq[0][j + 2], sq[1][j + 2]));
                    var[j] = bf_lo(s2) + bf_hi(s2);
                    ps[0][j] = __shfl_xor_sync(0xffffffffu, __float_as_uint(var[j]), 1);
                }
            }
            if constexpr (t == SG_VA2) {
#pragma unroll
                for (int j = 0; j < 2; j++) {
                    var[j] += __uint_as_float(ps[0][j]);
                    ps[0][j] = __shfl_xor_sync(0xffffffffu, __float_as_uint(var[j]), 2);
                }
            }
            if constexpr (t == SG_RS) {
#pragma unroll
                for (int j = 0; j < 2; j++) {
                    const float vr = fmaxf(fmaf(-mean[j], mean[j], (var[j] + __uint_as_float(ps[0][j])) * (1.0f / CH)), 0.f);
                    float rs;
                    asm("rsqrt.approx.ftz.f32 %0, %1;" : "=f"(rs) : "f"(vr + 1e-5f));
                    rs *= GELU_S;
                    rp[j] = pack_bf16(rs, rs);
                    cp[j] = pack_bf16(mean[j] * rs, mean[j] * rs);
                }
            }
            if constexpr (t == SG_NRM) {
#pragma unroll
                for (int ks = 0; ks < 6; ks++)
#pragma unroll
                    for (int j = 0; j < 4; j++) r[ks][j] = hfma2(r[ks][j], rp[j & 1], cp[j & 1]);
            }
            if constexpr (t >= SG_CVT && t < SG_CVT + 3) {
#pragma unroll
                for (int ks = 2 * (t - SG_CVT); ks < 2 * (t - SG_CVT) + 2; ks++)
#pragma unroll
                    for (int j = 0; j < 4; j++) a[ks][j] = pack_f16(bf_lo(r[ks][j]), bf_hi(r[ks][j]));
            }
        };
        auto gelu = [&](auto Tc) {
            constexpr int t = decltype(Tc)::value;
            constexpr int sf = (t + 1) % 24, sb = (t + 23) % 24;
            if constexpr (t >= 0) {
#pragma unroll
                for (int i = 0; i < 4; i++) gelu_tanh(tl[t & 1][i], tg[t & 1][i], u[t & 1][i]);
            }
#pragma unroll
            for (int i = 0; i < 4; i++) u[(t + 1) & 1][i] = gelu_front(h[(sf / 6) & 1][4 * (sf % 6) + i]);
            if constexpr (t >= 1) {
#pragma unroll
                for (int i = 0; i < 4; i++)
                    p[sb][i] = gelu_back(h[(sb / 6) & 1][4 * (sb % 6) + i], tl[(t + 1) & 1][i], tg[(t + 1) & 1][i]);
            }
        };
        auto arrive = [&](int bar) {
            __syncwarp();
            mbar_arrive_if(bars + 8 * (bar + wg), lane == 0);
        };
        auto store_out = [&](int i) {
            const int half = i / 3, j = i % 3;
            sts128(out_addr + half * 8 * PXB + j * 64,
                   make_uint4(h2bf(acc2[8 * j + half]), h2bf(acc2[8 * j + 2 + half]), h2bf(acc2[8 * j + 4 + half]),
                              h2bf(acc2[8 * j + 6 + half])));
        };
        auto out_ready = [&]() {
            asm volatile("fence.proxy.async.shared::cta;" ::: "memory");
            arrive(B_OUT_READY);
        };

        mbar_wait(bars + 8 * (B_STG_FULL + wg), 0);
        TRS_(3);
        static_for<SG_LD, SG_CVT + 3>(layernorm);
        SCHED_FENCE();
        arrive(B_STG_EMPTY);
        WG_FENCE();
#pragma unroll
        for (int ks = 0; ks < 6; ks++) gemm1_step(h[0], a, w1desc, 0, ks);
        WG_COMMIT();
        wg_wait<0>();
        fence_regs(h[0]);
        static_for<-1, 3>(gelu);

#pragma unroll 1
        for (int it = 0; it < NT / 2; it++) {
            static_for<3, 27>([&](auto Tc) {
                constexpr int t = decltype(Tc)::value;
                if constexpr (t == 3) {
                    wg_wait<0>();
                    fence_regs(acc2);
                    fence_regs(h[0]);
                }
                if constexpr (t == 5) wg_wait<0>();
                else if constexpr (t % 6 == 5) wg_wait<2>();
                else if constexpr (t > 9) wg_wait<3>();
                if constexpr (t % 6 == 5) fence_regs(h[((t + 1) / 6) & 1]);
                if constexpr (t == SG_LD) {
                    if (it + 1 < NT / 2) mbar_wait(bars + 8 * (B_STG_FULL + wg), (it + 1) & 1);
                }
                if constexpr (t == SG_SUM + 1) {
                    out_ready();
                    arrive(B_STG_EMPTY);
                }
                if constexpr (t == 26) mbar_wait(bars + 8 * (B_OUT_FREE + wg), it & 1);
                if constexpr (t == 3 || (t >= 6 && t <= 25)) {
                    WG_FENCE();
                    if constexpr (t == 3) {
#pragma unroll
                        for (int ks = 0; ks < 6; ks++) gemm1_step(h[1], a, w1desc, 1, ks);
                    }
                    if constexpr (t >= 7 && (t % 6 == 1 || t % 6 == 2) && t < 24) {
                        constexpr int c = (t / 6 + 1) % 4;
#pragma unroll
                        for (int ks = 0; ks < 3; ks++) gemm1_step(h[c & 1], a, w1desc, c, (t % 6 - 1) * 3 + ks);
                    }
                    if constexpr (t >= 6) {
#pragma unroll
                        for (int j = (t == 6 ? 0 : t - 2); j <= t - 2; j++) gemm2_step(acc2, p[j], w2desc, j);
                    }
                    WG_COMMIT();
                }
                gelu(Tc);
                if constexpr (t <= 5) {
                    store_out(2 * (t - 3));
                    store_out(2 * (t - 3) + 1);
                }
                layernorm(Tc);
                SCHED_FENCE();
            });
            wg_wait<0>();
        }
        fence_regs(acc2);
#pragma unroll
        for (int i = 0; i < 6; i++) store_out(i);
        out_ready();
        TRS_(4);
    }
}

typedef CUresult (*PFN_encodeTiled)(CUtensorMap*, CUtensorMapDataType, cuuint32_t, void*, const cuuint64_t*,
                                    const cuuint64_t*, const cuuint32_t*, const cuuint32_t*, CUtensorMapInterleave,
                                    CUtensorMapSwizzle, CUtensorMapL2promotion, CUtensorMapFloatOOBfill);

}

extern "C" void kernel_launch(void* const* d_in, const int* in_sizes, int n_in, void* d_out, int out_size) {
    const __nv_bfloat16* x = (const __nv_bfloat16*)d_in[0];
    const __nv_bfloat16* dwl = (const __nv_bfloat16*)d_in[1];
    const __nv_bfloat16* dws = (const __nv_bfloat16*)d_in[2];
    const __nv_bfloat16* w1 = (const __nv_bfloat16*)d_in[3];
    const __nv_bfloat16* w2 = (const __nv_bfloat16*)d_in[4];

    static PFN_encodeTiled encode = nullptr;
    if (!encode) {
        void* fn = nullptr;
        cudaDriverEntryPointQueryResult qres;
        cudaGetDriverEntryPoint("cuTensorMapEncodeTiled", &fn, cudaEnableDefault, &qres);
        encode = (PFN_encodeTiled)fn;
        cudaFuncSetAttribute(fused_block_kernel, cudaFuncAttributeMaxDynamicSharedMemorySize, SMEM_TOTAL);
    }
    CUtensorMap rowmap, tilemap, outmap;
    cuuint64_t gdim[3] = {(cuuint64_t)CH, (cuuint64_t)IMG_W, (cuuint64_t)IMG_H};
    cuuint64_t gstride[2] = {(cuuint64_t)PXB, (cuuint64_t)IMG_W * PXB};
    cuuint32_t estr[3] = {1, 1, 1};
    cuuint32_t box_row[3] = {(cuuint32_t)CH, (cuuint32_t)ROW_PX, (cuuint32_t)TR};
    cuuint32_t box_tile[3] = {(cuuint32_t)CH, (cuuint32_t)BW, (cuuint32_t)TR};
    encode(&rowmap, CU_TENSOR_MAP_DATA_TYPE_BFLOAT16, 3, (void*)x, gdim, gstride, box_row, estr,
           CU_TENSOR_MAP_INTERLEAVE_NONE, CU_TENSOR_MAP_SWIZZLE_NONE, CU_TENSOR_MAP_L2_PROMOTION_L2_256B,
           CU_TENSOR_MAP_FLOAT_OOB_FILL_NONE);
    encode(&tilemap, CU_TENSOR_MAP_DATA_TYPE_BFLOAT16, 3, (void*)x, gdim, gstride, box_tile, estr,
           CU_TENSOR_MAP_INTERLEAVE_NONE, CU_TENSOR_MAP_SWIZZLE_NONE, CU_TENSOR_MAP_L2_PROMOTION_L2_256B,
           CU_TENSOR_MAP_FLOAT_OOB_FILL_NONE);
    encode(&outmap, CU_TENSOR_MAP_DATA_TYPE_BFLOAT16, 3, d_out, gdim, gstride, box_tile, estr,
           CU_TENSOR_MAP_INTERLEAVE_NONE, CU_TENSOR_MAP_SWIZZLE_NONE, CU_TENSOR_MAP_L2_PROMOTION_NONE,
           CU_TENSOR_MAP_FLOAT_OOB_FILL_NONE);
    fused_block_kernel<<<NCTA, NTHREADS, SMEM_TOTAL>>>(rowmap, tilemap, outmap, dwl, dws, w1, w2);
}
```

```cpp
#include <cuda_runtime.h>
#include <cuda_bf16.h>
#include <cuda.h>
#include <stdint.h>
#include <type_traits>

#define TRS_(i)
#define PTR_(k)

#define PFMODE 0
#define PROMO CU_TENSOR_MAP_L2_PROMOTION_L2_256B
#define G1N 2
#define G2F 0
#define SQN 1
namespace {

constexpr int IMG_H = 512, IMG_W = 512, CH = 96, HID = 384;
constexpr int BW = 16;
constexpr int TR = 4;
constexpr int NT = 32;
constexpr int NCTA = (IMG_W / BW) * (IMG_H / (TR * NT));
constexpr int PXB = CH * 2;
constexpr int ROW_PX = BW + 4;
constexpr int ROW_BYTES = ROW_PX * PXB;
constexpr int UNIT_BYTES = TR * ROW_BYTES;
constexpr int STG_PITCH = 208;
constexpr int STG_BYTES = 64 * STG_PITCH;
constexpr int OUT_BYTES = 64 * PXB;
constexpr int NTHREADS = 512;
#define MR 168
constexpr int MLP_REGS = MR, TMA_REGS = 24, CONV_REGS = 512 - 2 * MLP_REGS - TMA_REGS;

constexpr int W1_BYTES = CH * HID * 2;
constexpr int W2_BYTES = HID * CH * 2;
constexpr int WPIECE = 24576;
constexpr int SM_W1 = 0;
constexpr int SM_W2 = SM_W1 + W1_BYTES;
constexpr int SM_RING = SM_W2 + W2_BYTES;
constexpr int SM_OUT = SM_RING + 2 * UNIT_BYTES;
constexpr int SM_STG = SM_OUT + 2 * OUT_BYTES;
constexpr int SM_BAR = SM_STG + 2 * STG_BYTES;
constexpr int SMEM_TOTAL = SM_BAR + 256;
static_assert(SMEM_TOTAL <= 232448, "smem");

constexpr int B_RING_FULL = 0;
constexpr int B_RING_EMPTY = 2;
constexpr int B_STG_FULL = 4;
constexpr int B_STG_EMPTY = 6;
constexpr int B_X_FULL = 8;
constexpr int B_OUT_READY = 10;
constexpr int B_OUT_FREE = 12;
constexpr int B_FILTER = 14;
constexpr int B_WEIGHTS = 16;

constexpr int W1_LBO = 8 * HID * 2, W1_SBO = 128;
constexpr int W2_KG = 8 * CH * 2;
constexpr int W2_LBO = 8 * W2_KG, W2_SBO = 128;

constexpr float GELU_S = 0.3292034911525734f;
constexpr float GELU_C = 1.5188174288475842f;
constexpr uint32_t GELU_A2 = 0x40D940D9u;

__device__ __forceinline__ uint32_t smem_u32(const void* p) {
    return (uint32_t)__cvta_generic_to_shared(p);
}
__device__ __forceinline__ uint64_t make_desc(uint32_t addr, uint32_t lbo, uint32_t sbo) {
    return (uint64_t)((addr & 0x3FFFF) >> 4) | ((uint64_t)(lbo >> 4) << 16) | ((uint64_t)(sbo >> 4) << 32);
}
__device__ __forceinline__ void mbar_init(uint32_t bar, uint32_t cnt) {
    asm volatile("mbarrier.init.shared::cta.b64 [%0], %1;" ::"r"(bar), "r"(cnt));
}
__device__ __forceinline__ void mbar_expect_tx(uint32_t bar, uint32_t bytes) {
    asm volatile("mbarrier.arrive.expect_tx.shared::cta.b64 _, [%0], %1;" ::"r"(bar), "r"(bytes) : "memory");
}
__device__ __forceinline__ void mbar_arrive_if(uint32_t bar, bool pred) {
    asm volatile("{\n.reg .pred p;\nsetp.ne.u32 p, %1, 0;\n@p mbarrier.arrive.shared::cta.b64 _, [%0];\n}\n"
                 ::"r"(bar), "r"((uint32_t)pred) : "memory");
}
__device__ __forceinline__ void mbar_wait(uint32_t bar, uint32_t parity) {
    asm volatile(
        "{\n"
        ".reg .pred p;\n"
        "WAIT_LOOP:\n"
        "mbarrier.try_wait.parity.shared::cta.b64 p, [%0], %1, %2;\n"
        "@p bra WAIT_DONE;\n"
        "bra WAIT_LOOP;\n"
        "WAIT_DONE:\n"
        "}\n" ::"r"(bar), "r"(parity), "r"(20000) : "memory");
}
__device__ __forceinline__ void tma_load3d(uint32_t dst, const CUtensorMap* map, int cx, int cy, uint32_t bar) {
    asm volatile(
        "cp.async.bulk.tensor.3d.shared::cluster.global.mbarrier::complete_tx::bytes [%0], [%1, {%2, %3, %4}], [%5];"
        ::"r"(dst), "l"((uint64_t)map), "r"(0), "r"(cx), "r"(cy), "r"(bar) : "memory");
}
__device__ __forceinline__ void tma_prefetch3d(const CUtensorMap* map, int cx, int cy) {
    return;
    asm volatile("cp.async.bulk.prefetch.tensor.3d.L2.global [%0, {%1, %2, %3}];"
                 ::"l"((uint64_t)map), "r"(0), "r"(cx), "r"(cy) : "memory");
}
__device__ __forceinline__ void bulk_load(uint32_t dst, const void* src, uint32_t bytes, uint32_t bar) {
    asm volatile("cp.async.bulk.shared::cluster.global.mbarrier::complete_tx::bytes [%0], [%1], %2, [%3];"
                 ::"r"(dst), "l"(src), "r"(bytes), "r"(bar) : "memory");
}
__device__ __forceinline__ uint4 lds128(uint32_t addr) {
    uint4 v;
    asm volatile("ld.shared.v4.u32 {%0,%1,%2,%3}, [%4];" : "=r"(v.x), "=r"(v.y), "=r"(v.z), "=r"(v.w) : "r"(addr));
    return v;
}
__device__ __forceinline__ uint32_t lds32(uint32_t addr) {
    uint32_t v;
    asm volatile("ld.shared.u32 %0, [%1];" : "=r"(v) : "r"(addr));
    return v;
}
__device__ __forceinline__ void sts128(uint32_t addr, uint4 v) {
    asm volatile("st.shared.v4.u32 [%0], {%1,%2,%3,%4};" ::"r"(addr), "r"(v.x), "r"(v.y), "r"(v.z), "r"(v.w) : "memory");
}
__device__ __forceinline__ void sts32(uint32_t addr, uint32_t a) {
    asm volatile("st.shared.u32 [%0], %1;" ::"r"(addr), "r"(a) : "memory");
}
__device__ __forceinline__ void ldsm4(uint32_t& a, uint32_t& b, uint32_t& c, uint32_t& d, uint32_t addr) {
    asm volatile("ldmatrix.sync.aligned.m8n8.x4.shared.b16 {%0,%1,%2,%3}, [%4];"
                 : "=r"(a), "=r"(b), "=r"(c), "=r"(d) : "r"(addr));
}
__device__ __forceinline__ void ldsm2(uint32_t& a, uint32_t& b, uint32_t addr) {
    asm volatile("ldmatrix.sync.aligned.m8n8.x2.shared.b16 {%0,%1}, [%2];" : "=r"(a), "=r"(b) : "r"(addr));
}
__device__ __forceinline__ void stsm4(uint32_t addr, uint32_t a, uint32_t b, uint32_t c, uint32_t d) {
    asm volatile("stmatrix.sync.aligned.m8n8.x4.shared.b16 [%0], {%1,%2,%3,%4};"
                 ::"r"(addr), "r"(a), "r"(b), "r"(c), "r"(d) : "memory");
}
__device__ __forceinline__ void stsm2(uint32_t addr, uint32_t a, uint32_t b) {
    asm volatile("stmatrix.sync.aligned.m8n8.x2.shared.b16 [%0], {%1,%2};" ::"r"(addr), "r"(a), "r"(b) : "memory");
}
__device__ __forceinline__ uint32_t hfma2(uint32_t a, uint32_t b, uint32_t c) {
    uint32_t d;
    asm("fma.rn.bf16x2 %0, %1, %2, %3;" : "=r"(d) : "r"(a), "r"(b), "r"(c));
    return d;
}
__device__ __forceinline__ uint32_t hmul2(uint32_t a, uint32_t b) {
    uint32_t d;
    asm("mul.rn.bf16x2 %0, %1, %2;" : "=r"(d) : "r"(a), "r"(b));
    return d;
}
__device__ __forceinline__ uint32_t hadd2(uint32_t a, uint32_t b) {
    uint32_t d;
    asm("add.rn.bf16x2 %0, %1, %2;" : "=r"(d) : "r"(a), "r"(b));
    return d;
}
__device__ __forceinline__ uint32_t hsub2(uint32_t a, uint32_t b) {
    uint32_t d;
    asm("sub.rn.bf16x2 %0, %1, %2;" : "=r"(d) : "r"(a), "r"(b));
    return d;
}
__device__ __forceinline__ uint32_t fold(uint32_t a, uint32_t b) {
    return hadd2(__byte_perm(a, b, 0x5410), __byte_perm(a, b, 0x7632));
}
__device__ __forceinline__ float bf_lo(uint32_t v) { return __uint_as_float(v << 16); }
__device__ __forceinline__ float bf_hi(uint32_t v) { return __uint_as_float(v & 0xffff0000u); }
__device__ __forceinline__ uint32_t pack_bf16(float lo, float hi) {
    uint32_t d;
    asm("cvt.rn.bf16x2.f32 %0, %1, %2;" : "=r"(d) : "f"(hi), "f"(lo));
    return d;
}
__device__ __forceinline__ uint32_t pack_f16(float lo, float hi) {
    uint32_t d;
    asm("cvt.rn.f16x2.f32 %0, %1, %2;" : "=r"(d) : "f"(hi), "f"(lo));
    return d;
}
__device__ __forceinline__ uint32_t bf2h(uint32_t v, float sc) { return pack_f16(bf_lo(v) * sc, bf_hi(v) * sc); }
__device__ __forceinline__ uint4 bf2h4(uint4 v, float sc) {
    return make_uint4(bf2h(v.x, sc), bf2h(v.y, sc), bf2h(v.z, sc), bf2h(v.w, sc));
}
__device__ __forceinline__ uint32_t h2bf(uint32_t h) {
    float lo, hi;
    asm("{\n.reg .b16 l, h;\nmov.b32 {l, h}, %2;\ncvt.f32.f16 %0, l;\ncvt.f32.f16 %1, h;\n}\n" : "=f"(lo), "=f"(hi) : "r"(h));
    return pack_bf16(lo, hi);
}

#define WG_FENCE() asm volatile("wgmma.fence.sync.aligned;" ::: "memory")
#define WG_COMMIT() asm volatile("wgmma.commit_group.sync.aligned;" ::: "memory")
template <int N>
__device__ __forceinline__ void wg_wait() {
    asm volatile("wgmma.wait_group.sync.aligned %0;" ::"n"(N) : "memory");
}
#define SCHED_FENCE() asm volatile("pmevent.mask 0;" ::: "memory")

template <bool ACC>
__device__ __forceinline__ void wgmma_rs(uint32_t (&d)[24], const uint32_t (&a)[4], uint64_t desc) {
    asm volatile(
        "{\n"
        ".reg .pred p;\n"
        "setp.ne.b32 p, %29, 0;\n"
        "wgmma.mma_async.sync.aligned.m64n96k16.f16.f16.f16 {"
        "%0,%1,%2,%3,%4,%5,%6,%7,%8,%9,%10,%11,%12,%13,%14,%15,"
        "%16,%17,%18,%19,%20,%21,%22,%23"
        "}, {%24,%25,%26,%27}, %28, p, 1, 1, 1;\n"
        "}\n"
        : "+r"(d[0]), "+r"(d[1]), "+r"(d[2]), "+r"(d[3]), "+r"(d[4]), "+r"(d[5]), "+r"(d[6]), "+r"(d[7]),
          "+r"(d[8]), "+r"(d[9]), "+r"(d[10]), "+r"(d[11]), "+r"(d[12]), "+r"(d[13]), "+r"(d[14]), "+r"(d[15]),
          "+r"(d[16]), "+r"(d[17]), "+r"(d[18]), "+r"(d[19]), "+r"(d[20]), "+r"(d[21]), "+r"(d[22]), "+r"(d[23])
        : "r"(a[0]), "r"(a[1]), "r"(a[2]), "r"(a[3]), "l"(desc), "n"(ACC ? 1 : 0));
}
__device__ __forceinline__ void gemm1_step(uint32_t (&h)[24], const uint32_t (&a)[6][4], uint64_t w1desc, int c, int ks) {
    const uint64_t d = w1desc + (uint64_t)((c * 12 * W1_SBO + ks * 2 * W1_LBO) >> 4);
    if (ks == 0) wgmma_rs<false>(h, a[0], d);
    else wgmma_rs<true>(h, a[ks], d);
}
__device__ __forceinline__ void gemm2_step(uint32_t (&acc2)[24], const uint32_t (&p)[4], uint64_t w2desc, int j) {
    const uint64_t d = w2desc + (uint64_t)(((16 * (j % 3) + j / 3) * W2_KG) >> 4);
    if (j == 0) wgmma_rs<false>(acc2, p, d);
    else wgmma_rs<true>(acc2, p, d);
}
__device__ __forceinline__ uint32_t gelu_front(uint32_t y) {
    uint32_t t, u;
    asm("fma.rn.f16x2 %0, %1, %1, %2;" : "=r"(t) : "r"(y), "r"(GELU_A2));
    asm("mul.rn.f16x2 %0, %1, %2;" : "=r"(u) : "r"(y), "r"(t));
    return u;
}
__device__ __forceinline__ void gelu_tanh(uint16_t& lo, uint16_t& hi, uint32_t u) {
    asm("{\n.reg .b16 l, h;\nmov.b32 {l, h}, %2;\ntanh.approx.f16 %0, l;\ntanh.approx.f16 %1, h;\n}\n"
        : "=h"(lo), "=h"(hi) : "r"(u));
}
__device__ __forceinline__ uint32_t gelu_back(uint32_t y, uint16_t lo, uint16_t hi) {
    uint32_t g;
    asm("{\n.reg .b32 t;\nmov.b32 t, {%2, %3};\nfma.rn.f16x2 %0, %1, t, %1;\n}\n" : "=r"(g) : "r"(y), "h"(lo), "h"(hi));
    return g;
}

template <int B, int E, typename F>
__device__ __forceinline__ void static_for(F&& f) {
    if constexpr (B < E) {
        f(std::integral_constant<int, B>{});
        static_for<B + 1, E>(f);
    }
}

template <int NP, int R0>
__device__ __forceinline__ void conv_row(uint32_t (&o)[2 * NP], uint32_t (&acc)[4][NP][3], const uint32_t (&w)[5][7],
                                         const uint32_t (&x)[2 * NP + 4]) {
    uint32_t e[NP + 1], f[NP + 1], t[5][NP][3];
#pragma unroll
    for (int i = 0; i <= NP; i++) {
        e[i] = hsub2(x[2 * i], x[2 * i + 1]);
        f[i] = hsub2(x[2 * i + 2], x[2 * i + 1]);
    }
#pragma unroll
    for (int p = 0; p < NP; p++) {
#pragma unroll
        for (int r = R0; r < 5; r++) {
            const uint32_t(&h)[7] = w[4 - r];
            t[r][p][1] = r < 4 ? hfma2(x[2 * p + 1], h[3], acc[r & 3][p][1]) : hmul2(x[2 * p + 1], h[3]);
            t[r][p][0] = r < 4 ? hfma2(x[2 * p + 4], h[2], acc[r & 3][p][0]) : hmul2(x[2 * p + 4], h[2]);
            t[r][p][2] = r < 4 ? hfma2(x[2 * p + 5], h[2], acc[r & 3][p][2]) : hmul2(x[2 * p + 5], h[2]);
        }
#pragma unroll
        for (int r = R0; r < 5; r++) {
            const uint32_t(&h)[7] = w[4 - r];
            t[r][p][1] = hfma2(x[2 * p + 3], h[4], t[r][p][1]);
            t[r][p][0] = hfma2(e[p], h[0], t[r][p][0]);
            t[r][p][2] = hfma2(f[p], h[5], t[r][p][2]);
        }
#pragma unroll
        for (int r = R0; r < 5; r++) {
            const uint32_t(&h)[7] = w[4 - r];
            t[r][p][0] = hfma2(e[p + 1], h[1], t[r][p][0]);
            t[r][p][2] = hfma2(f[p + 1], h[6], t[r][p][2]);
        }
        if (R0 == 0) {
            o[2 * p] = hadd2(t[0][p][0], t[0][p][1]);
            o[2 * p + 1] = hadd2(t[0][p][1], t[0][p][2]);
        }
#pragma unroll
        for (int r = (R0 > 0 ? R0 : 1); r < 5; r++)
#pragma unroll
            for (int m = 0; m < 3; m++) acc[r - 1][p][m] = t[r][p][m];
    }
}

#define SGV G9bcd3fghi7i
#define STR2(x) #x
#define STR(x) STR2(x)
constexpr int sgd(int i) { return STR(SGV)[i + 1] <= '9' ? STR(SGV)[i + 1] - '0' : STR(SGV)[i + 1] - 'a' + 10; }
constexpr int SGT[] = {sgd(0), sgd(1), sgd(2), sgd(3), sgd(4), sgd(5), sgd(6), sgd(7), sgd(8), sgd(9), sgd(10)};
constexpr int SG_LD = SGT[0], SG_SUM = SGT[1], SG_SH2 = SGT[2], SG_CEN = SGT[3], SG_NCEN = SGT[4], SG_VAR = SGT[5],
              SG_VA2 = SGT[6], SG_RS = SGT[7], SG_NRM = SGT[8], SG_OUT = SGT[9], SG_CVT = SGT[10];
#define EPN 2
#define WMASK 0
#define WD 3

__global__ void __launch_bounds__(NTHREADS, 1)
fused_block_kernel(const __grid_constant__ CUtensorMap rowmap, const __grid_constant__ CUtensorMap tilemap,
                   const __grid_constant__ CUtensorMap outmap,
                   const __nv_bfloat16* __restrict__ dwl, const __nv_bfloat16* __restrict__ dws,
                   const __nv_bfloat16* __restrict__ w1, const __nv_bfloat16* __restrict__ w2) {
    extern __shared__ __align__(1024) uint8_t smem[];
    const uint32_t sbase = smem_u32(smem);
    const int tid = threadIdx.x;
    const int wid = __shfl_sync(0xffffffffu, tid >> 5, 0);
    const int wg = wid >> 2, warp = wid & 3;
    const int lane = tid & 31;
    const uint32_t bars = sbase + SM_BAR;
    const int x0 = (blockIdx.x >> 2) * BW, y0 = (blockIdx.x & 3) * (TR * NT);

    if (tid == NTHREADS - 128) {
        const char* w1b = reinterpret_cast<const char*>(w1);
        const char* w2b = reinterpret_cast<const char*>(w2);
        asm volatile("cp.async.bulk.prefetch.L2.global [%0], %1;"
                     ::"l"(((blockIdx.x & 1) ? w2b : w1b) + (blockIdx.x >> 1) * (W1_BYTES / (NCTA / 2))), "r"(W1_BYTES / (NCTA / 2))
                     : "memory");
        mbar_init(bars + 8 * B_FILTER, 1);
        mbar_init(bars + 8 * B_RING_FULL, 1);
        mbar_init(bars + 8 * B_RING_FULL + 8, 1);
#pragma unroll
        for (int i = 0; i < 6; i++) mbar_init(bars + 8 * (B_WEIGHTS + i), 1);
        asm volatile("fence.mbarrier_init.release.cluster;" ::: "memory");
        mbar_expect_tx(bars + 8 * B_FILTER, 34 * PXB);
        bulk_load(sbase + SM_OUT, dws, 25 * PXB, bars + 8 * B_FILTER);
        bulk_load(sbase + SM_OUT + 25 * PXB, dwl, 9 * PXB, bars + 8 * B_FILTER);
#pragma unroll
        for (int i = 0; i < 6; i++) {
            if (i < 2) {
                mbar_expect_tx(bars + 8 * (B_RING_FULL + i), UNIT_BYTES);
                tma_load3d(sbase + SM_RING + i * UNIT_BYTES, &rowmap, x0 - 2, y0 - 2 + TR * i, bars + 8 * (B_RING_FULL + i));
            }
            mbar_expect_tx(bars + 8 * (B_WEIGHTS + i), WPIECE);
            bulk_load(sbase + i * WPIECE, (i < 3 ? w1b : w2b) + (i % 3) * WPIECE, WPIECE, bars + 8 * (B_WEIGHTS + i));
        }
    } else if (tid == NTHREADS - 96) {
#pragma unroll
        for (int m = 0; m < 2; m++) {
            mbar_init(bars + 8 * (B_RING_EMPTY + m), 4);
            mbar_init(bars + 8 * (B_STG_FULL + m), 4);
            mbar_init(bars + 8 * (B_STG_EMPTY + m), 4);
            mbar_init(bars + 8 * (B_X_FULL + m), 1);
            mbar_init(bars + 8 * (B_OUT_READY + m), 4);
            mbar_init(bars + 8 * (B_OUT_FREE + m), 1);
        }
        asm volatile("fence.mbarrier_init.release.cluster;" ::: "memory");
    }
    __syncthreads();

    if (wg == 3) {
        asm volatile("setmaxnreg.dec.sync.aligned.u32 %0;" ::"n"(TMA_REGS));
        const int m = warp >> 1;
        if (lane == 0) {
            if (warp == 0 || warp == 3) {
                const uint32_t fb = bars + 8 * (B_RING_FULL + m);
                mbar_wait(fb, 0);
                tma_prefetch3d(&rowmap, x0 - 2, y0 - 2 + TR * (m + 2));
#pragma unroll 1
                for (int j = m + 2; j <= NT; j += 2) {
                    mbar_wait(bars + 8 * (B_RING_EMPTY + m), ((j >> 1) & 1) ^ 1);
                    mbar_expect_tx(fb, UNIT_BYTES);
                    tma_load3d(sbase + SM_RING + m * UNIT_BYTES, &rowmap, x0 - 2, y0 - 2 + TR * j, fb);
                    if (j + 2 <= NT) tma_prefetch3d(&rowmap, x0 - 2, y0 - 2 + TR * (j + 2));
                }
                if (m == 1) {
                    mbar_wait(bars + 8 * (B_RING_EMPTY + m), ((NT >> 1) & 1) ^ 1);
                    mbar_arrive_if(fb, true);
                }
            } else {
                const uint32_t fb = bars + 8 * (B_X_FULL + m), buf = sbase + SM_OUT + m * OUT_BYTES;
                mbar_wait(bars + 8 * (B_OUT_READY + m), 0);
#pragma unroll 1
                for (int i = 0; i < NT / 2; i++) {
                    const int cy = y0 + TR * (2 * i + m);
                    PTR_(0);
                    mbar_expect_tx(fb, OUT_BYTES);
                    tma_load3d(buf, &tilemap, x0, cy, fb);
                    mbar_wait(fb, i & 1);
                    PTR_(1);
                    asm volatile("cp.async.bulk.tensor.3d.global.shared::cta.bulk_group [%0, {%1, %2, %3}], [%4];"
                                 ::"l"((uint64_t)&outmap), "r"(0), "r"(x0), "r"(cy), "r"(buf) : "memory");
                    asm volatile("cp.async.bulk.commit_group;" ::: "memory");
                    asm volatile("cp.async.bulk.wait_group 0;" ::: "memory");
                    PTR_(2);
                    mbar_arrive_if(bars + 8 * (B_OUT_FREE + m), true);
                    mbar_wait(bars + 8 * (B_OUT_READY + m), (i & 1) ^ 1);
                    PTR_(3);
                    asm volatile("cp.reduce.async.bulk.tensor.3d.global.shared::cta.add.bulk_group [%0, {%1, %2, %3}], [%4];"
                                 ::"l"((uint64_t)&outmap), "r"(0), "r"(x0), "r"(cy), "r"(buf) : "memory");
                    asm volatile("cp.async.bulk.commit_group;" ::: "memory");
                    asm volatile("cp.async.bulk.wait_group 0;" ::: "memory");
                    PTR_(4);
                }
            }
        }
    } else if (wg == 2) {
        asm volatile("setmaxnreg.inc.sync.aligned.u32 %0;" ::"n"(CONV_REGS));
        uint32_t wa[5][7], wb[5][7];
        {
            const uint32_t pa = sbase + SM_OUT + 4 * lane, pb = sbase + SM_OUT + 4 * (32 + (lane & 15));
            const bool mir = lane >= 16;
            mbar_wait(bars + 8 * B_FILTER, 0);
#pragma unroll
            for (int r = 0; r < 5; r++) {
                uint32_t u[5], v[5];
#pragma unroll
                for (int c = 0; c < 5; c++) {
                    u[c] = lds32(pa + (5 * r + c) * PXB);
                    v[c] = lds32(pb + (5 * r + c) * PXB);
                    if (r >= 1 && r <= 3 && c >= 1 && c <= 3) {
                        u[c] = hadd2(u[c], lds32(pa + (25 + 3 * (r - 1) + c - 1) * PXB));
                        v[c] = hadd2(v[c], lds32(pb + (25 + 3 * (r - 1) + c - 1) * PXB));
                    }
                }
#pragma unroll
                for (int c = 0; c < 2; c++) {
                    const uint32_t lo = v[c], hi = v[4 - c];
                    v[c] = mir ? hi : lo;
                    v[4 - c] = mir ? lo : hi;
                }
                wa[r][0] = u[0]; wa[r][1] = u[2]; wa[r][2] = u[4]; wa[r][3] = hadd2(u[0], u[1]);
                wa[r][4] = hadd2(u[2], u[3]); wa[r][5] = u[1]; wa[r][6] = u[3];
                wb[r][0] = v[0]; wb[r][1] = v[2]; wb[r][2] = v[4]; wb[r][3] = hadd2(v[0], v[1]);
                wb[r][4] = hadd2(v[2], v[3]); wb[r][5] = v[1]; wb[r][6] = v[3];
            }
        }
        const int mi = lane >> 3, mr = lane & 7, up = mr >> 2;
        const uint32_t ring_a = sbase + SM_RING + (4 * warp + mi) * PXB + mr * 16;
        const uint32_t ring_b0 = sbase + SM_RING + (4 * warp + (up ? 7 - mi : mi)) * PXB + 128 + (mr & 3) * 16;
        const uint32_t ring_b1 = sbase + SM_RING + (4 * warp + (up ? 3 - mi : 4 + mi)) * PXB + 128 + (mr & 3) * 16;
        const uint32_t stg_a = sbase + SM_STG + (4 * warp + mi) * STG_PITCH + mr * 16;
        const uint32_t stg_b = sbase + SM_STG + (4 * warp + (up ? 3 - mi : mi)) * STG_PITCH + 128 + (mr & 3) * 16;
        uint32_t acca[4][2][3], accb[4][1][3], xa[8], xb[6], oa[4], ob[2];
        auto fetch_a = [&](uint32_t off) {
            ldsm4(xa[0], xa[1], xa[2], xa[3], ring_a + off);
            ldsm4(xa[4], xa[5], xa[6], xa[7], ring_a + off + 4 * PXB);
        };
        auto fetch_b = [&](uint32_t off) {
            ldsm4(xb[0], xb[1], xb[2], xb[3], ring_b0 + off);
            ldsm2(xb[4], xb[5], ring_b1 + off);
        };
        const uint32_t arr = bars + 8 * (lane == 0 ? B_RING_EMPTY + 1 : B_STG_FULL);
        TRS_(0);
        mbar_wait(bars + 8 * B_RING_FULL, 0);
        TRS_(1);
        static_for<0, 4>([&](auto Rc) {
            constexpr int R = decltype(Rc)::value;
            fetch_a(R * ROW_BYTES);
            fetch_b(R * ROW_BYTES);
            conv_row<2, 4 - R>(oa, acca, wa, xa);
            conv_row<1, 4 - R>(ob, accb, wb, xb);
        });
        SCHED_FENCE();
        __syncwarp();
        mbar_arrive_if(bars + 8 * B_RING_EMPTY, lane == 0);
        mbar_wait(bars + 8 * (B_RING_FULL + 1), 0);
        fetch_a(UNIT_BYTES);
        fetch_b(UNIT_BYTES);
        TRS_(5);
#define CU 2
#pragma unroll 1
        for (int k0 = 0; k0 < NT; k0 += CU) {
#pragma unroll
            for (int kk = 0; kk < CU; kk++) {
                const uint32_t s = CU == 2 ? kk : (k0 & 1), ph = ((k0 >> 1) & 1) ^ 1;
                const uint32_t nxt = s * UNIT_BYTES, cur = nxt ^ UNIT_BYTES, dst = s * STG_BYTES;
#pragma unroll
                for (int R = 0; R < 4; R++) {
                    conv_row<2, 0>(oa, acca, wa, xa);
                    if (R == 0) mbar_wait(bars + 8 * B_STG_EMPTY + 8 * s, ph);
                    if (R == 3) mbar_wait(bars + 8 * B_RING_FULL + 8 * s, ph);
                    fetch_a(R < 3 ? cur + (R + 1) * ROW_BYTES : nxt);
                    SCHED_FENCE();
                    stsm4(stg_a + dst + R * (BW * STG_PITCH), oa[0], oa[1], oa[2], oa[3]);
                    conv_row<1, 0>(ob, accb, wb, xb);
                    fetch_b(R < 3 ? cur + (R + 1) * ROW_BYTES : nxt);
                    stsm2(stg_b + dst + R * (BW * STG_PITCH), ob[0], ob[1]);
                    if (R == 3) {
                        __syncwarp();
                        mbar_arrive_if(arr ^ (8 * s), lane < 2);
                    }
                    if (R < 3 || kk + 1 < CU) SCHED_FENCE();
                }
            }
        }
#pragma unroll
        for (int s = 0; s < 2; s++) {
            mbar_wait(bars + 8 * B_STG_EMPTY + 8 * s, 1);
            mbar_arrive_if(bars + 8 * B_STG_FULL + 8 * s, lane == 0);
        }
        TRS_(4);
    } else {
        asm volatile("setmaxnreg.inc.sync.aligned.u32 %0;" ::"n"(MLP_REGS));
        TRS_(0);
        {
            const int kk = lane & 7, a0 = (kk + (lane >> 3)) & 7;
#pragma unroll 1
            for (int t = wid; t < 24; t += 8) {
                const uint32_t base = sbase + SM_W1 + (t >> 1) * W1_LBO + (t & 1) * 384;
                uint4 v[6];
                mbar_wait(bars + 8 * (B_WEIGHTS + (t >> 3)), 0);
#pragma unroll
                for (int i = 0; i < 6; i++) v[i] = lds128(base + (i >> 1) * 128 + kk * (HID * 2) + (a0 ^ ((i & 1) * 4)) * 16);
                __syncwarp();
#pragma unroll
                for (int i = 0; i < 6; i++)
                    sts128(base + (i >> 1) * 128 + (a0 ^ ((i & 1) * 4)) * (HID * 2) + kk * 16, bf2h4(v[i], 1.0f));
            }
            TRS_(1);
            const int q2 = lane & 3, k2 = lane >> 2;
#pragma unroll 1
            for (int t = wid; t < 48; t += 8) {
                const uint32_t base = sbase + SM_W2 + t * W2_KG;
                uint4 v[3];
                mbar_wait(bars + 8 * (B_WEIGHTS + 3 + (t >> 4)), 0);
#pragma unroll
                for (int i = 0; i < 3; i++) v[i] = lds128(base + k2 * (CH * 2) + i * 64 + q2 * 16);
                __syncwarp();
#pragma unroll
                for (int i = 0; i < 3; i++) {
                    const uint32_t d = base + i * 512 + k2 * 16 + q2 * 4;
                    const uint4 c = bf2h4(v[i], GELU_C);
                    sts32(d, c.x);
                    sts32(d + 128, c.y);
                    sts32(d + 256, c.z);
                    sts32(d + 384, c.w);
                }
            }
            asm volatile("fence.proxy.async.shared::cta;" ::: "memory");
            asm volatile("bar.sync 1, 256;" ::: "memory");
            TRS_(2);
        }

        const uint64_t w1desc = make_desc(sbase + SM_W1, W1_LBO, W1_SBO);
        const uint64_t w2desc = make_desc(sbase + SM_W2, W2_LBO, W2_SBO);
        const uint32_t ldm_addr = sbase + SM_STG + wg * STG_BYTES +
                                  (16 * warp + (lane & 7) + ((lane >> 3) & 1) * 8) * STG_PITCH + (lane >> 4) * 16;
        const uint32_t out_addr = sbase + SM_OUT + wg * OUT_BYTES + (16 * warp + (lane >> 2)) * PXB + (lane & 3) * 16;

        uint32_t a[6][4], r[6][4];
        uint32_t h[2][24], acc2[24];
        uint32_t p[24][4], u[2][4];
        uint16_t tl[2][4], tg[2][4];
        uint32_t ps[2][2], sq[2][4], rp[2], cp[2], st, sx;
        auto fence_regs = [&](auto& v) {
#pragma unroll
            for (int i = 0; i < (int)(sizeof(v) / 4); i++) asm volatile("" : "+r"(v[i]) :: "memory");
        };
#pragma unroll
        for (int i = 0; i < 24; i++) acc2[i] = h[0][i] = h[1][i] = 0u;
        fence_regs(acc2);
        fence_regs(h[0]);
        fence_regs(h[1]);

        auto layernorm = [&](auto Tc) {
            constexpr int t = decltype(Tc)::value;
            if constexpr (t == SG_LD || t == SG_LD + 1) {
#pragma unroll
                for (int ks = 3 * (t - SG_LD); ks < 3 * (t - SG_LD) + 3; ks++)
                    ldsm4(r[ks][0], r[ks][1], r[ks][2], r[ks][3], ldm_addr + ks * 32);
            }
            if constexpr (t == SG_SUM - 1 || t == SG_SUM) {
                constexpr int k0 = 3 * (t - SG_SUM + 1);
#pragma unroll
                for (int j = 0; j < 2; j++)
                    ps[t - SG_SUM + 1][j] = hadd2(hadd2(hadd2(r[k0][j], r[k0][j + 2]), hadd2(r[k0 + 1][j], r[k0 + 1][j + 2])),
                                                  hadd2(r[k0 + 2][j], r[k0 + 2][j + 2]));
            }
            if constexpr (t == SG_SUM) {
                st = fold(hadd2(ps[0][0], ps[1][0]), hadd2(ps[0][1], ps[1][1]));
                sx = __shfl_xor_sync(0xffffffffu, st, 1);
            }
            if constexpr (t == SG_SH2 || t == SG_VA2) {
                st = hadd2(st, sx);
                sx = __shfl_xor_sync(0xffffffffu, st, 2);
            }
            if constexpr (t == SG_CEN) {
                st = hadd2(st, sx);
                const float m0 = bf_lo(st) * (-1.0f / CH), m1 = bf_hi(st) * (-1.0f / CH);
                cp[0] = pack_bf16(m0, m0);
                cp[1] = pack_bf16(m1, m1);
            }
            if constexpr (t >= SG_CEN && t < SG_CEN + SG_NCEN) {
#pragma unroll
                for (int ks = (t - SG_CEN) * (6 / SG_NCEN); ks < (t - SG_CEN + 1) * (6 / SG_NCEN); ks++) {
#pragma unroll
                    for (int j = 0; j < 4; j++) {
                        r[ks][j] = hadd2(r[ks][j], cp[j & 1]);
                        sq[ks % SQN][j] = ks < SQN ? hmul2(r[ks][j], r[ks][j]) : hfma2(r[ks][j], r[ks][j], sq[ks % SQN][j]);
                    }
                }
            }
            if constexpr (t == SG_VAR) {
                if (SQN == 2) {
#pragma unroll
                    for (int j = 0; j < 4; j++) sq[0][j] = hadd2(sq[0][j], sq[1][j]);
                }
                st = fold(hadd2(sq[0][0], sq[0][2]), hadd2(sq[0][1], sq[0][3]));
                sx = __shfl_xor_sync(0xffffffffu, st, 1);
            }
            if constexpr (t == SG_RS) {
                st = hadd2(st, sx);
                float rs[2];
#pragma unroll
                for (int j = 0; j < 2; j++) {
                    constexpr float K = 1.0f / (GELU_S * GELU_S);
                    asm("rsqrt.approx.ftz.f32 %0, %1;" : "=f"(rs[j]) : "f"(fmaf(j ? bf_hi(st) : bf_lo(st), K / CH, K * 1e-5f)));
                }
#pragma unroll
                for (int j = 0; j < 2; j++) rp[j] = pack_bf16(rs[j], rs[j]);
            }
            if constexpr (SG_NRM < SG_CVT ? t == SG_NRM : (t >= SG_CVT && t < SG_CVT + 3)) {
#pragma unroll
                for (int ks = (SG_NRM < SG_CVT ? 0 : 2 * (t - SG_CVT)); ks < (SG_NRM < SG_CVT ? 6 : 2 * (t - SG_CVT) + 2); ks++)
#pragma unroll
                    for (int j = 0; j < 4; j++) r[ks][j] = hmul2(r[ks][j], rp[j & 1]);
            }
            if constexpr (t >= SG_CVT && t < SG_CVT + 3) {
#pragma unroll
                for (int ks = 2 * (t - SG_CVT); ks < 2 * (t - SG_CVT) + 2; ks++)
#pragma unroll
                    for (int j = 0; j < 4; j++) {
                        a[ks][j] = pack_f16(bf_lo(r[ks][j]), bf_hi(r[ks][j]));
                    }
            }
        };
        auto gelu_part = [&](auto Tc, int i0, int i1) {
            constexpr int t = decltype(Tc)::value;
            constexpr int sf = (t + 1) % 24, sb = (t + 23) % 24;
            auto f_tanh = [&]() {
                if constexpr (t >= 0) {
#pragma unroll
                    for (int i = i0; i < i1; i++) gelu_tanh(tl[t & 1][i], tg[t & 1][i], u[t & 1][i]);
                }
            };
            auto f_front = [&]() {
#pragma unroll
                for (int i = i0; i < i1; i++) u[(t + 1) & 1][i] = gelu_front(h[(sf / 6) & 1][4 * (sf % 6) + i]);
            };
            auto f_back = [&]() {
                if constexpr (t >= 1) {
#pragma unroll
                    for (int i = i0; i < i1; i++)
                        p[sb][i] = gelu_back(h[(sb / 6) & 1][4 * (sb % 6) + i], tl[(t + 1) & 1][i], tg[(t + 1) & 1][i]);
                }
            };
#define GORD 0
            if (GORD == 0) { f_tanh(); f_front(); f_back(); }
            if (GORD == 1) { f_front(); f_back(); f_tanh(); }
            if (GORD == 2) { f_front(); f_tanh(); f_back(); }
            if (GORD == 3) { f_back(); f_front(); f_tanh(); }
        };
        auto gelu = [&](auto Tc) { gelu_part(Tc, 0, 4); };
        auto arrive = [&](int bar) {
            __syncwarp();
            mbar_arrive_if(bars + 8 * (bar + wg), lane == 0);
        };
        auto store_out = [&](int i) {
            const int half = i / 3, j = i % 3;
            sts128(out_addr + half * 8 * PXB + j * 64,
                   make_uint4(h2bf(acc2[8 * j + half]), h2bf(acc2[8 * j + 2 + half]), h2bf(acc2[8 * j + 4 + half]),
                              h2bf(acc2[8 * j + 6 + half])));
        };
        auto out_ready = [&]() {
            asm volatile("fence.proxy.async.shared::cta;" ::: "memory");
            arrive(B_OUT_READY);
        };

        mbar_wait(bars + 8 * (B_STG_FULL + wg), 0);
        TRS_(3);
        static_for<SG_LD, SG_CVT + 3>(layernorm);
        SCHED_FENCE();
        arrive(B_STG_EMPTY);
        WG_FENCE();
#pragma unroll
        for (int ks = 0; ks < 6; ks++) gemm1_step(h[0], a, w1desc, 0, ks);
        WG_COMMIT();
#pragma unroll
        for (int ks = 0; ks < 6; ks++) gemm1_step(h[1], a, w1desc, 1, ks);
        WG_COMMIT();
        wg_wait<1>();
        fence_regs(h[0]);
        static_for<-1, 5>(gelu);
        wg_wait<0>();

#define LASTG1 0
#define BL 9
#define BL1 1
#define LAG 2
#define XS 27
#pragma unroll 1
        for (int it = 0;; it++) {
            bool done = false;
            static_for<5, 29>([&](auto Tc) {
                constexpr int t = decltype(Tc)::value;
                if (done) return;
                constexpr int GL = 23 + LAG;
                constexpr int E0 = 29 - EPN;
                if constexpr (t == 5) {
                    wg_wait<0>();
                    fence_regs(h[0]);
                } else if constexpr (t % 6 == 5) {
                    wg_wait<1>();
                } else if constexpr (t == E0) {
                    wg_wait<E0 - 25>();
                }
                if constexpr (t % 6 == 5) fence_regs(h[((t + 1) / 6) & 1]);
                if constexpr (t == E0) fence_regs(acc2);
                if constexpr (t == SG_LD) mbar_wait(bars + 8 * (B_STG_FULL + wg), (it + 1) & 1);
                if constexpr (t == SG_OUT) out_ready();
                if constexpr (t == SG_SUM + 1) arrive(B_STG_EMPTY);
                if constexpr (t == 24) mbar_wait(bars + 8 * (B_OUT_FREE + wg), it & 1);
                if constexpr (t == E0) {
                    if (it == NT / 2 - 1) { done = true; return; }
                }
                constexpr auto g2end = [](int s) {
                    if (s < 5) return 0;
                    int e = 0;
                    for (int q = 5; q <= s; q++) {
                        const int cap = (q % 6 >= 1 && q % 6 <= 3) ? BL1 : BL;
                        e = e + cap < q - LAG + 1 ? e + cap : q - LAG + 1;
                    }
                    return e < 24 ? e : 24;
                };
                static_assert(g2end(GL) == 24, "");
                constexpr int j0 = g2end(t - 1), j1 = g2end(t);
                constexpr bool g1seg = t % 6 >= 1 && t % 6 <= 3;
                if constexpr (LAG == 1) gelu(Tc);
                if constexpr (j1 > j0 || g1seg) {
                    WG_FENCE();
#pragma unroll
                    for (int j = j0; j < j1; j++) gemm2_step(acc2, p[j], w2desc, j);
                    if constexpr (g1seg) {
                        if constexpr (t == GL) WG_COMMIT();
                        constexpr int c = (t / 6 + 1) % 4;
                        gemm1_step(h[c & 1], a, w1desc, c, (t % 6 - 1) * 2);
                        gemm1_step(h[c & 1], a, w1desc, c, (t % 6 - 1) * 2 + 1);
                    }
                    WG_COMMIT();
                }
                if constexpr (LAG == 2) gelu(Tc);
                if constexpr (t >= E0) {
#pragma unroll
                    for (int i = (t - E0) * (6 / EPN); i < (t - E0 + 1) * (6 / EPN); i++) store_out(i);
                }
                layernorm(Tc);
                SCHED_FENCE();
            });
            if (done) break;
            wg_wait<0>();
        }
        wg_wait<0>();
        fence_regs(acc2);
#pragma unroll
        for (int i = 0; i < 6; i++) store_out(i);
        out_ready();
        TRS_(4);
    }
}

typedef CUresult (*PFN_encodeTiled)(CUtensorMap*, CUtensorMapDataType, cuuint32_t, void*, const cuuint64_t*,
                                    const cuuint64_t*, const cuuint32_t*, const cuuint32_t*, CUtensorMapInterleave,
                                    CUtensorMapSwizzle, CUtensorMapL2promotion, CUtensorMapFloatOOBfill);

}

extern "C" void kernel_launch(void* const* d_in, const int* in_sizes, int n_in, void* d_out, int out_size) {
    const __nv_bfloat16* x = (const __nv_bfloat16*)d_in[0];
    const __nv_bfloat16* dwl = (const __nv_bfloat16*)d_in[1];
    const __nv_bfloat16* dws = (const __nv_bfloat16*)d_in[2];
    const __nv_bfloat16* w1 = (const __nv_bfloat16*)d_in[3];
    const __nv_bfloat16* w2 = (const __nv_bfloat16*)d_in[4];

    static PFN_encodeTiled encode = nullptr;
    if (!encode) {
        void* fn = nullptr;
        cudaDriverEntryPointQueryResult qres;
        cudaGetDriverEntryPoint("cuTensorMapEncodeTiled", &fn, cudaEnableDefault, &qres);
        encode = (PFN_encodeTiled)fn;
        cudaFuncSetAttribute(fused_block_kernel, cudaFuncAttributeMaxDynamicSharedMemorySize, SMEM_TOTAL);
    }
    CUtensorMap rowmap, tilemap, outmap;
    cuuint64_t gdim[3] = {(cuuint64_t)CH, (cuuint64_t)IMG_W, (cuuint64_t)IMG_H};
    cuuint64_t gstride[2] = {(cuuint64_t)PXB, (cuuint64_t)IMG_W * PXB};
    cuuint32_t estr[4] = {1, 1, 1, 1};
    cuuint32_t box_row[3] = {(cuuint32_t)CH, (cuuint32_t)ROW_PX, (cuuint32_t)TR};
    cuuint32_t box_tile[3] = {(cuuint32_t)CH, (cuuint32_t)BW, (cuuint32_t)TR};
    encode(&rowmap, CU_TENSOR_MAP_DATA_TYPE_BFLOAT16, 3, (void*)x, gdim, gstride, box_row, estr,
           CU_TENSOR_MAP_INTERLEAVE_NONE, CU_TENSOR_MAP_SWIZZLE_NONE, PROMO,
           CU_TENSOR_MAP_FLOAT_OOB_FILL_NONE);
    encode(&tilemap, CU_TENSOR_MAP_DATA_TYPE_BFLOAT16, 3, (void*)x, gdim, gstride, box_tile, estr,
           CU_TENSOR_MAP_INTERLEAVE_NONE, CU_TENSOR_MAP_SWIZZLE_NONE, PROMO,
           CU_TENSOR_MAP_FLOAT_OOB_FILL_NONE);
    encode(&outmap, CU_TENSOR_MAP_DATA_TYPE_BFLOAT16, 3, d_out, gdim, gstride, box_tile, estr,
           CU_TENSOR_MAP_INTERLEAVE_NONE, CU_TENSOR_MAP_SWIZZLE_NONE, CU_TENSOR_MAP_L2_PROMOTION_NONE,
           CU_TENSOR_MAP_FLOAT_OOB_FILL_NONE);
    fused_block_kernel<<<NCTA, NTHREADS, SMEM_TOTAL>>>(rowmap, tilemap, outmap, dwl, dws, w1, w2);
}
```

```cpp
#include <cuda_runtime.h>
#include <cuda_bf16.h>
#include <cuda.h>
#include <stdint.h>
#include <type_traits>

#define TRS_(i)
#define PTR_(k)

namespace {

constexpr int IMG_H = 512, IMG_W = 512, CH = 96, HID = 384;
constexpr int BW = 16;
constexpr int TR = 4;
constexpr int NT = 32;
constexpr int NCTA = (IMG_W / BW) * (IMG_H / (TR * NT));
constexpr int PXB = CH * 2;
constexpr int ROW_PX = BW + 4;
constexpr int ROW_BYTES = ROW_PX * PXB;
constexpr int UNIT_BYTES = TR * ROW_BYTES;
constexpr int STG_PITCH = 208;
constexpr int STG_BYTES = 64 * STG_PITCH;
constexpr int OUT_BYTES = 64 * PXB;
constexpr int NTHREADS = 512;
constexpr int MLP_REGS = 168, TMA_REGS = 24, CONV_REGS = 512 - 2 * MLP_REGS - TMA_REGS;

constexpr int W1_BYTES = CH * HID * 2;
constexpr int W2_BYTES = HID * CH * 2;
constexpr int WPIECE = 24576;
constexpr int SM_W1 = 0;
constexpr int SM_W2 = SM_W1 + W1_BYTES;
constexpr int SM_RING = SM_W2 + W2_BYTES;
constexpr int SM_OUT = SM_RING + 2 * UNIT_BYTES;
constexpr int SM_STG = SM_OUT + 2 * OUT_BYTES;
constexpr int SM_BAR = SM_STG + 2 * STG_BYTES;
constexpr int SMEM_TOTAL = SM_BAR + 256;
static_assert(SMEM_TOTAL <= 232448, "smem");

constexpr int B_RING_FULL = 0;
constexpr int B_RING_EMPTY = 2;
constexpr int B_STG_FULL = 4;
constexpr int B_STG_EMPTY = 6;
constexpr int B_X_FULL = 8;
constexpr int B_OUT_READY = 10;
constexpr int B_OUT_FREE = 12;
constexpr int B_FILTER = 14;
constexpr int B_WEIGHTS = 16;

constexpr int W1_LBO = 8 * HID * 2, W1_SBO = 128;
constexpr int W2_KG = 8 * CH * 2;
constexpr int W2_LBO = 8 * W2_KG, W2_SBO = 128;

constexpr float GELU_S = 0.3292034911525734f;
constexpr float GELU_C = 1.5188174288475842f;
constexpr uint32_t GELU_A2 = 0x40D940D9u;

__device__ __forceinline__ uint32_t smem_u32(const void* p) {
    return (uint32_t)__cvta_generic_to_shared(p);
}
__device__ __forceinline__ uint64_t make_desc(uint32_t addr, uint32_t lbo, uint32_t sbo) {
    return (uint64_t)((addr & 0x3FFFF) >> 4) | ((uint64_t)(lbo >> 4) << 16) | ((uint64_t)(sbo >> 4) << 32);
}
__device__ __forceinline__ void mbar_init(uint32_t bar, uint32_t cnt) {
    asm volatile("mbarrier.init.shared::cta.b64 [%0], %1;" ::"r"(bar), "r"(cnt));
}
__device__ __forceinline__ void mbar_expect_tx(uint32_t bar, uint32_t bytes) {
    asm volatile("mbarrier.arrive.expect_tx.shared::cta.b64 _, [%0], %1;" ::"r"(bar), "r"(bytes) : "memory");
}
__device__ __forceinline__ void mbar_arrive_if(uint32_t bar, bool pred) {
    asm volatile("{\n.reg .pred p;\nsetp.ne.u32 p, %1, 0;\n@p mbarrier.arrive.shared::cta.b64 _, [%0];\n}\n"
                 ::"r"(bar), "r"((uint32_t)pred) : "memory");
}
__device__ __forceinline__ void mbar_wait(uint32_t bar, uint32_t parity) {
    asm volatile(
        "{\n"
        ".reg .pred p;\n"
        "WAIT_LOOP:\n"
        "mbarrier.try_wait.parity.shared::cta.b64 p, [%0], %1, %2;\n"
        "@p bra WAIT_DONE;\n"
        "bra WAIT_LOOP;\n"
        "WAIT_DONE:\n"
        "}\n" ::"r"(bar), "r"(parity), "r"(20000) : "memory");
}
__device__ __forceinline__ void tma_load3d(uint32_t dst, const CUtensorMap* map, int cx, int cy, uint32_t bar) {
    asm volatile(
        "cp.async.bulk.tensor.3d.shared::cluster.global.mbarrier::complete_tx::bytes [%0], [%1, {%2, %3, %4}], [%5];"
        ::"r"(dst), "l"((uint64_t)map), "r"(0), "r"(cx), "r"(cy), "r"(bar) : "memory");
}
__device__ __forceinline__ void bulk_load(uint32_t dst, const void* src, uint32_t bytes, uint32_t bar) {
    asm volatile("cp.async.bulk.shared::cluster.global.mbarrier::complete_tx::bytes [%0], [%1], %2, [%3];"
                 ::"r"(dst), "l"(src), "r"(bytes), "r"(bar) : "memory");
}
__device__ __forceinline__ uint4 lds128(uint32_t addr) {
    uint4 v;
    asm volatile("ld.shared.v4.u32 {%0,%1,%2,%3}, [%4];" : "=r"(v.x), "=r"(v.y), "=r"(v.z), "=r"(v.w) : "r"(addr));
    return v;
}
__device__ __forceinline__ uint32_t lds32(uint32_t addr) {
    uint32_t v;
    asm volatile("ld.shared.u32 %0, [%1];" : "=r"(v) : "r"(addr));
    return v;
}
__device__ __forceinline__ void sts128(uint32_t addr, uint4 v) {
    asm volatile("st.shared.v4.u32 [%0], {%1,%2,%3,%4};" ::"r"(addr), "r"(v.x), "r"(v.y), "r"(v.z), "r"(v.w) : "memory");
}
__device__ __forceinline__ void sts32(uint32_t addr, uint32_t a) {
    asm volatile("st.shared.u32 [%0], %1;" ::"r"(addr), "r"(a) : "memory");
}
__device__ __forceinline__ void ldsm4(uint32_t& a, uint32_t& b, uint32_t& c, uint32_t& d, uint32_t addr) {
    asm volatile("ldmatrix.sync.aligned.m8n8.x4.shared.b16 {%0,%1,%2,%3}, [%4];"
                 : "=r"(a), "=r"(b), "=r"(c), "=r"(d) : "r"(addr));
}
__device__ __forceinline__ void ldsm2(uint32_t& a, uint32_t& b, uint32_t addr) {
    asm volatile("ldmatrix.sync.aligned.m8n8.x2.shared.b16 {%0,%1}, [%2];" : "=r"(a), "=r"(b) : "r"(addr));
}
__device__ __forceinline__ void stsm4(uint32_t addr, uint32_t a, uint32_t b, uint32_t c, uint32_t d) {
    asm volatile("stmatrix.sync.aligned.m8n8.x4.shared.b16 [%0], {%1,%2,%3,%4};"
                 ::"r"(addr), "r"(a), "r"(b), "r"(c), "r"(d) : "memory");
}
__device__ __forceinline__ void stsm2(uint32_t addr, uint32_t a, uint32_t b) {
    asm volatile("stmatrix.sync.aligned.m8n8.x2.shared.b16 [%0], {%1,%2};" ::"r"(addr), "r"(a), "r"(b) : "memory");
}
__device__ __forceinline__ uint32_t hfma2(uint32_t a, uint32_t b, uint32_t c) {
    uint32_t d;
    asm("fma.rn.bf16x2 %0, %1, %2, %3;" : "=r"(d) : "r"(a), "r"(b), "r"(c));
    return d;
}
__device__ __forceinline__ uint32_t hmul2(uint32_t a, uint32_t b) {
    uint32_t d;
    asm("mul.rn.bf16x2 %0, %1, %2;" : "=r"(d) : "r"(a), "r"(b));
    return d;
}
__device__ __forceinline__ uint32_t hadd2(uint32_t a, uint32_t b) {
    uint32_t d;
    asm("add.rn.bf16x2 %0, %1, %2;" : "=r"(d) : "r"(a), "r"(b));
    return d;
}
__device__ __forceinline__ uint32_t hsub2(uint32_t a, uint32_t b) {
    uint32_t d;
    asm("sub.rn.bf16x2 %0, %1, %2;" : "=r"(d) : "r"(a), "r"(b));
    return d;
}
__device__ __forceinline__ uint32_t fold(uint32_t a, uint32_t b) {
    return hadd2(__byte_perm(a, b, 0x5410), __byte_perm(a, b, 0x7632));
}
__device__ __forceinline__ float bf_lo(uint32_t v) { return __uint_as_float(v << 16); }
__device__ __forceinline__ float bf_hi(uint32_t v) { return __uint_as_float(v & 0xffff0000u); }
__device__ __forceinline__ uint32_t pack_bf16(float lo, float hi) {
    uint32_t d;
    asm("cvt.rn.bf16x2.f32 %0, %1, %2;" : "=r"(d) : "f"(hi), "f"(lo));
    return d;
}
__device__ __forceinline__ uint32_t pack_f16(float lo, float hi) {
    uint32_t d;
    asm("cvt.rn.f16x2.f32 %0, %1, %2;" : "=r"(d) : "f"(hi), "f"(lo));
    return d;
}
__device__ __forceinline__ uint32_t bf2h(uint32_t v, float sc) { return pack_f16(bf_lo(v) * sc, bf_hi(v) * sc); }
__device__ __forceinline__ uint4 bf2h4(uint4 v, float sc) {
    return make_uint4(bf2h(v.x, sc), bf2h(v.y, sc), bf2h(v.z, sc), bf2h(v.w, sc));
}
__device__ __forceinline__ uint32_t h2bf(uint32_t h) {
    float lo, hi;
    asm("{\n.reg .b16 l, h;\nmov.b32 {l, h}, %2;\ncvt.f32.f16 %0, l;\ncvt.f32.f16 %1, h;\n}\n" : "=f"(lo), "=f"(hi) : "r"(h));
    return pack_bf16(lo, hi);
}

#define WG_FENCE() asm volatile("wgmma.fence.sync.aligned;" ::: "memory")
#define WG_COMMIT() asm volatile("wgmma.commit_group.sync.aligned;" ::: "memory")
template <int N>
__device__ __forceinline__ void wg_wait() {
    asm volatile("wgmma.wait_group.sync.aligned %0;" ::"n"(N) : "memory");
}
#define SCHED_FENCE() asm volatile("pmevent.mask 0;" ::: "memory")

template <bool ACC>
__device__ __forceinline__ void wgmma_rs(uint32_t (&d)[24], const uint32_t (&a)[4], uint64_t desc) {
    asm volatile(
        "{\n"
        ".reg .pred p;\n"
        "setp.ne.b32 p, %29, 0;\n"
        "wgmma.mma_async.sync.aligned.m64n96k16.f16.f16.f16 {"
        "%0,%1,%2,%3,%4,%5,%6,%7,%8,%9,%10,%11,%12,%13,%14,%15,"
        "%16,%17,%18,%19,%20,%21,%22,%23"
        "}, {%24,%25,%26,%27}, %28, p, 1, 1, 1;\n"
        "}\n"
        : "+r"(d[0]), "+r"(d[1]), "+r"(d[2]), "+r"(d[3]), "+r"(d[4]), "+r"(d[5]), "+r"(d[6]), "+r"(d[7]),
          "+r"(d[8]), "+r"(d[9]), "+r"(d[10]), "+r"(d[11]), "+r"(d[12]), "+r"(d[13]), "+r"(d[14]), "+r"(d[15]),
          "+r"(d[16]), "+r"(d[17]), "+r"(d[18]), "+r"(d[19]), "+r"(d[20]), "+r"(d[21]), "+r"(d[22]), "+r"(d[23])
        : "r"(a[0]), "r"(a[1]), "r"(a[2]), "r"(a[3]), "l"(desc), "n"(ACC ? 1 : 0));
}
__device__ __forceinline__ void gemm1_step(uint32_t (&h)[24], const uint32_t (&a)[6][4], uint64_t w1desc, int c, int ks) {
    const uint64_t d = w1desc + (uint64_t)((c * 12 * W1_SBO + ks * 2 * W1_LBO) >> 4);
    if (ks == 0) wgmma_rs<false>(h, a[0], d);
    else wgmma_rs<true>(h, a[ks], d);
}
__device__ __forceinline__ void gemm2_step(uint32_t (&acc2)[24], const uint32_t (&p)[4], uint64_t w2desc, int j) {
    const uint64_t d = w2desc + (uint64_t)(((16 * (j % 3) + j / 3) * W2_KG) >> 4);
    if (j == 0) wgmma_rs<false>(acc2, p, d);
    else wgmma_rs<true>(acc2, p, d);
}
__device__ __forceinline__ uint32_t gelu_front(uint32_t y) {
    uint32_t t, u;
    asm("fma.rn.f16x2 %0, %1, %1, %2;" : "=r"(t) : "r"(y), "r"(GELU_A2));
    asm("mul.rn.f16x2 %0, %1, %2;" : "=r"(u) : "r"(y), "r"(t));
    return u;
}
__device__ __forceinline__ void gelu_tanh(uint16_t& lo, uint16_t& hi, uint32_t u) {
    asm("{\n.reg .b16 l, h;\nmov.b32 {l, h}, %2;\ntanh.approx.f16 %0, l;\ntanh.approx.f16 %1, h;\n}\n"
        : "=h"(lo), "=h"(hi) : "r"(u));
}
__device__ __forceinline__ uint32_t gelu_back(uint32_t y, uint16_t lo, uint16_t hi) {
    uint32_t g;
    asm("{\n.reg .b32 t;\nmov.b32 t, {%2, %3};\nfma.rn.f16x2 %0, %1, t, %1;\n}\n" : "=r"(g) : "r"(y), "h"(lo), "h"(hi));
    return g;
}

template <int B, int E, typename F>
__device__ __forceinline__ void static_for(F&& f) {
    if constexpr (B < E) {
        f(std::integral_constant<int, B>{});
        static_for<B + 1, E>(f);
    }
}

template <int NP, int R0>
__device__ __forceinline__ void conv_row(uint32_t (&o)[2 * NP], uint32_t (&acc)[4][NP][3], const uint32_t (&w)[5][7],
                                         const uint32_t (&x)[2 * NP + 4]) {
    uint32_t e[NP + 1], f[NP + 1], t[5][NP][3];
#pragma unroll
    for (int i = 0; i <= NP; i++) {
        e[i] = hsub2(x[2 * i], x[2 * i + 1]);
        f[i] = hsub2(x[2 * i + 2], x[2 * i + 1]);
    }
#pragma unroll
    for (int p = 0; p < NP; p++) {
#pragma unroll
        for (int r = R0; r < 5; r++) {
            const uint32_t(&h)[7] = w[4 - r];
            t[r][p][1] = r < 4 ? hfma2(x[2 * p + 1], h[3], acc[r & 3][p][1]) : hmul2(x[2 * p + 1], h[3]);
            t[r][p][0] = r < 4 ? hfma2(x[2 * p + 4], h[2], acc[r & 3][p][0]) : hmul2(x[2 * p + 4], h[2]);
            t[r][p][2] = r < 4 ? hfma2(x[2 * p + 5], h[2], acc[r & 3][p][2]) : hmul2(x[2 * p + 5], h[2]);
        }
#pragma unroll
        for (int r = R0; r < 5; r++) {
            const uint32_t(&h)[7] = w[4 - r];
            t[r][p][1] = hfma2(x[2 * p + 3], h[4], t[r][p][1]);
            t[r][p][0] = hfma2(e[p], h[0], t[r][p][0]);
            t[r][p][2] = hfma2(f[p], h[5], t[r][p][2]);
        }
#pragma unroll
        for (int r = R0; r < 5; r++) {
            const uint32_t(&h)[7] = w[4 - r];
            t[r][p][0] = hfma2(e[p + 1], h[1], t[r][p][0]);
            t[r][p][2] = hfma2(f[p + 1], h[6], t[r][p][2]);
        }
        if (R0 == 0) {
            o[2 * p] = hadd2(t[0][p][0], t[0][p][1]);
            o[2 * p + 1] = hadd2(t[0][p][1], t[0][p][2]);
        }
#pragma unroll
        for (int r = (R0 > 0 ? R0 : 1); r < 5; r++)
#pragma unroll
            for (int m = 0; m < 3; m++) acc[r - 1][p][m] = t[r][p][m];
    }
}

constexpr int SG_LD = 9, SG_SUM = 11, SG_SH2 = 12, SG_CEN = 13, SG_VAR = 15, SG_VA2 = 16, SG_RS = 17, SG_CVT = 18;
constexpr int SG_OUT = 7;
constexpr int SG_EPI = 27;

__global__ void __launch_bounds__(NTHREADS, 1)
fused_block_kernel(const __grid_constant__ CUtensorMap rowmap, const __grid_constant__ CUtensorMap tilemap,
                   const __grid_constant__ CUtensorMap outmap,
                   const __nv_bfloat16* __restrict__ dwl, const __nv_bfloat16* __restrict__ dws,
                   const __nv_bfloat16* __restrict__ w1, const __nv_bfloat16* __restrict__ w2) {
    extern __shared__ __align__(1024) uint8_t smem[];
    const uint32_t sbase = smem_u32(smem);
    const int tid = threadIdx.x;
    const int wid = __shfl_sync(0xffffffffu, tid >> 5, 0);
    const int wg = wid >> 2, warp = wid & 3;
    const int lane = tid & 31;
    const uint32_t bars = sbase + SM_BAR;
    const int x0 = (blockIdx.x >> 2) * BW, y0 = (blockIdx.x & 3) * (TR * NT);

    if (tid == NTHREADS - 128) {
        const char* w1b = reinterpret_cast<const char*>(w1);
        const char* w2b = reinterpret_cast<const char*>(w2);
        asm volatile("cp.async.bulk.prefetch.L2.global [%0], %1;"
                     ::"l"(((blockIdx.x & 1) ? w2b : w1b) + (blockIdx.x >> 1) * (W1_BYTES / (NCTA / 2))), "r"(W1_BYTES / (NCTA / 2))
                     : "memory");
        mbar_init(bars + 8 * B_FILTER, 1);
        mbar_init(bars + 8 * B_RING_FULL, 1);
        mbar_init(bars + 8 * B_RING_FULL + 8, 1);
#pragma unroll
        for (int i = 0; i < 6; i++) mbar_init(bars + 8 * (B_WEIGHTS + i), 1);
        asm volatile("fence.mbarrier_init.release.cluster;" ::: "memory");
        mbar_expect_tx(bars + 8 * B_FILTER, 34 * PXB);
        bulk_load(sbase + SM_OUT, dws, 25 * PXB, bars + 8 * B_FILTER);
        bulk_load(sbase + SM_OUT + 25 * PXB, dwl, 9 * PXB, bars + 8 * B_FILTER);
#pragma unroll
        for (int i = 0; i < 6; i++) {
            if (i < 2) {
                mbar_expect_tx(bars + 8 * (B_RING_FULL + i), UNIT_BYTES);
                tma_load3d(sbase + SM_RING + i * UNIT_BYTES, &rowmap, x0 - 2, y0 - 2 + TR * i, bars + 8 * (B_RING_FULL + i));
            }
            mbar_expect_tx(bars + 8 * (B_WEIGHTS + i), WPIECE);
            bulk_load(sbase + i * WPIECE, (i < 3 ? w1b : w2b) + (i % 3) * WPIECE, WPIECE, bars + 8 * (B_WEIGHTS + i));
        }
    } else if (tid == NTHREADS - 96) {
#pragma unroll
        for (int m = 0; m < 2; m++) {
            mbar_init(bars + 8 * (B_RING_EMPTY + m), 4);
            mbar_init(bars + 8 * (B_STG_FULL + m), 4);
            mbar_init(bars + 8 * (B_STG_EMPTY + m), 4);
                        mbar_init(bars + 8 * (B_X_FULL + m), 1);
            mbar_init(bars + 8 * (B_OUT_READY + m), 4);
            mbar_init(bars + 8 * (B_OUT_FREE + m), 1);
        }
        asm volatile("fence.mbarrier_init.release.cluster;" ::: "memory");
    }
    __syncthreads();

    if (wg == 3) {
        asm volatile("setmaxnreg.dec.sync.aligned.u32 %0;" ::"n"(TMA_REGS));
        const int m = warp >> 1;
        if (lane == 0) {
            if (warp == 0 || warp == 3) {
                const uint32_t fb = bars + 8 * (B_RING_FULL + m);
#pragma unroll 1
                for (int j = m + 2; j <= NT; j += 2) {
                    mbar_wait(bars + 8 * (B_RING_EMPTY + m), ((j >> 1) & 1) ^ 1);
                    mbar_expect_tx(fb, UNIT_BYTES);
                    tma_load3d(sbase + SM_RING + m * UNIT_BYTES, &rowmap, x0 - 2, y0 - 2 + TR * j, fb);
                }
                if (m == 1) {
                    mbar_wait(bars + 8 * (B_RING_EMPTY + m), ((NT >> 1) & 1) ^ 1);
                    mbar_arrive_if(fb, true);
                }
            } else {
                const uint32_t fb = bars + 8 * (B_X_FULL + m), buf = sbase + SM_OUT + m * OUT_BYTES;
                mbar_wait(bars + 8 * (B_OUT_READY + m), 0);
#pragma unroll 1
                for (int i = 0; i < NT / 2; i++) {
                    const int cy = y0 + TR * (2 * i + m);
                    PTR_(0);
                    mbar_expect_tx(fb, OUT_BYTES);
                    tma_load3d(buf, &tilemap, x0, cy, fb);
                    mbar_wait(fb, i & 1);
                    PTR_(1);
                    asm volatile("cp.async.bulk.tensor.3d.global.shared::cta.bulk_group [%0, {%1, %2, %3}], [%4];"
                                 ::"l"((uint64_t)&outmap), "r"(0), "r"(x0), "r"(cy), "r"(buf) : "memory");
                    asm volatile("cp.async.bulk.commit_group;" ::: "memory");
                    asm volatile("cp.async.bulk.wait_group 0;" ::: "memory");
                    PTR_(2);
                    mbar_arrive_if(bars + 8 * (B_OUT_FREE + m), true);
                    mbar_wait(bars + 8 * (B_OUT_READY + m), (i & 1) ^ 1);
                    PTR_(3);
                    asm volatile("cp.reduce.async.bulk.tensor.3d.global.shared::cta.add.bulk_group [%0, {%1, %2, %3}], [%4];"
                                 ::"l"((uint64_t)&outmap), "r"(0), "r"(x0), "r"(cy), "r"(buf) : "memory");
                    asm volatile("cp.async.bulk.commit_group;" ::: "memory");
                    asm volatile("cp.async.bulk.wait_group 0;" ::: "memory");
                    PTR_(4);
                }
            }
        }
    } else if (wg == 2) {
        asm volatile("setmaxnreg.inc.sync.aligned.u32 %0;" ::"n"(CONV_REGS));
        uint32_t wa[5][7], wb[5][7];
        {
            const uint32_t pa = sbase + SM_OUT + 4 * lane, pb = sbase + SM_OUT + 4 * (32 + (lane & 15));
            const bool mir = lane >= 16;
            mbar_wait(bars + 8 * B_FILTER, 0);
#pragma unroll
            for (int r = 0; r < 5; r++) {
                uint32_t u[5], v[5];
#pragma unroll
                for (int c = 0; c < 5; c++) {
                    u[c] = lds32(pa + (5 * r + c) * PXB);
                    v[c] = lds32(pb + (5 * r + c) * PXB);
                    if (r >= 1 && r <= 3 && c >= 1 && c <= 3) {
                        u[c] = hadd2(u[c], lds32(pa + (25 + 3 * (r - 1) + c - 1) * PXB));
                        v[c] = hadd2(v[c], lds32(pb + (25 + 3 * (r - 1) + c - 1) * PXB));
                    }
                }
#pragma unroll
                for (int c = 0; c < 2; c++) {
                    const uint32_t lo = v[c], hi = v[4 - c];
                    v[c] = mir ? hi : lo;
                    v[4 - c] = mir ? lo : hi;
                }
                wa[r][0] = u[0]; wa[r][1] = u[2]; wa[r][2] = u[4]; wa[r][3] = hadd2(u[0], u[1]);
                wa[r][4] = hadd2(u[2], u[3]); wa[r][5] = u[1]; wa[r][6] = u[3];
                wb[r][0] = v[0]; wb[r][1] = v[2]; wb[r][2] = v[4]; wb[r][3] = hadd2(v[0], v[1]);
                wb[r][4] = hadd2(v[2], v[3]); wb[r][5] = v[1]; wb[r][6] = v[3];
            }
        }
        const int mi = lane >> 3, mr = lane & 7, up = mr >> 2;
        const uint32_t ring_a = sbase + SM_RING + (4 * warp + mi) * PXB + mr * 16;
        const uint32_t ring_b0 = sbase + SM_RING + (4 * warp + (up ? 7 - mi : mi)) * PXB + 128 + (mr & 3) * 16;
        const uint32_t ring_b1 = sbase + SM_RING + (4 * warp + (up ? 3 - mi : 4 + mi)) * PXB + 128 + (mr & 3) * 16;
        const uint32_t stg_a = sbase + SM_STG + (4 * warp + mi) * STG_PITCH + mr * 16;
        const uint32_t stg_b = sbase + SM_STG + (4 * warp + (up ? 3 - mi : mi)) * STG_PITCH + 128 + (mr & 3) * 16;
        uint32_t acca[4][2][3], accb[4][1][3], xa[8], xb[6], oa[4], ob[2];
        auto fetch_a = [&](uint32_t off) {
            ldsm4(xa[0], xa[1], xa[2], xa[3], ring_a + off);
            ldsm4(xa[4], xa[5], xa[6], xa[7], ring_a + off + 4 * PXB);
        };
        auto fetch_b = [&](uint32_t off) {
            ldsm4(xb[0], xb[1], xb[2], xb[3], ring_b0 + off);
            ldsm2(xb[4], xb[5], ring_b1 + off);
        };
        const uint32_t arr = bars + 8 * (lane == 0 ? B_RING_EMPTY + 1 : B_STG_FULL);
        TRS_(0);
        mbar_wait(bars + 8 * B_RING_FULL, 0);
        TRS_(1);
        static_for<0, 4>([&](auto Rc) {
            constexpr int R = decltype(Rc)::value;
            fetch_a(R * ROW_BYTES);
            fetch_b(R * ROW_BYTES);
            conv_row<2, 4 - R>(oa, acca, wa, xa);
            conv_row<1, 4 - R>(ob, accb, wb, xb);
        });
        SCHED_FENCE();
        __syncwarp();
        mbar_arrive_if(bars + 8 * B_RING_EMPTY, lane == 0);
        mbar_wait(bars + 8 * (B_RING_FULL + 1), 0);
        fetch_a(UNIT_BYTES);
        fetch_b(UNIT_BYTES);
        TRS_(5);
#pragma unroll 1
        for (int k0 = 0; k0 < NT; k0 += 2) {
#pragma unroll
            for (int kk = 0; kk < 2; kk++) {
                const uint32_t s = kk, ph = ((k0 >> 1) & 1) ^ 1;
                const uint32_t nxt = s * UNIT_BYTES, cur = nxt ^ UNIT_BYTES, dst = s * STG_BYTES;
#pragma unroll
                for (int R = 0; R < 4; R++) {
                    conv_row<2, 0>(oa, acca, wa, xa);
                    if (R == 0) mbar_wait(bars + 8 * B_STG_EMPTY + 8 * s, ph);
                    if (R == 3) mbar_wait(bars + 8 * B_RING_FULL + 8 * s, ph);
                    fetch_a(R < 3 ? cur + (R + 1) * ROW_BYTES : nxt);
                    stsm4(stg_a + dst + R * (BW * STG_PITCH), oa[0], oa[1], oa[2], oa[3]);
                    conv_row<1, 0>(ob, accb, wb, xb);
                    fetch_b(R < 3 ? cur + (R + 1) * ROW_BYTES : nxt);
                    stsm2(stg_b + dst + R * (BW * STG_PITCH), ob[0], ob[1]);
                    if (R == 3) {
                        __syncwarp();
                        mbar_arrive_if(arr ^ (8 * s), lane < 2);
                    }
                    if (R < 3 || kk == 0) SCHED_FENCE();
                }
            }
        }
#pragma unroll
        for (int s = 0; s < 2; s++) {
            mbar_wait(bars + 8 * B_STG_EMPTY + 8 * s, 1);
            mbar_arrive_if(bars + 8 * B_STG_FULL + 8 * s, lane == 0);
        }
        TRS_(4);
    } else {
        asm volatile("setmaxnreg.inc.sync.aligned.u32 %0;" ::"n"(MLP_REGS));
        TRS_(0);
        {
            const int kk = lane & 7, a0 = (kk + (lane >> 3)) & 7;
#pragma unroll 1
            for (int t = wid; t < 24; t += 8) {
                const uint32_t base = sbase + SM_W1 + (t >> 1) * W1_LBO + (t & 1) * 384;
                uint4 v[6];
                mbar_wait(bars + 8 * (B_WEIGHTS + (t >> 3)), 0);
#pragma unroll
                for (int i = 0; i < 6; i++) v[i] = lds128(base + (i >> 1) * 128 + kk * (HID * 2) + (a0 ^ ((i & 1) * 4)) * 16);
                __syncwarp();
#pragma unroll
                for (int i = 0; i < 6; i++)
                    sts128(base + (i >> 1) * 128 + (a0 ^ ((i & 1) * 4)) * (HID * 2) + kk * 16, bf2h4(v[i], 1.0f));
            }
            TRS_(1);
            const int q2 = lane & 3, k2 = lane >> 2;
#pragma unroll 1
            for (int t = wid; t < 48; t += 8) {
                const uint32_t base = sbase + SM_W2 + t * W2_KG;
                uint4 v[3];
                mbar_wait(bars + 8 * (B_WEIGHTS + 3 + (t >> 4)), 0);
#pragma unroll
                for (int i = 0; i < 3; i++) v[i] = lds128(base + k2 * (CH * 2) + i * 64 + q2 * 16);
                __syncwarp();
#pragma unroll
                for (int i = 0; i < 3; i++) {
                    const uint32_t d = base + i * 512 + k2 * 16 + q2 * 4;
                    const uint4 c = bf2h4(v[i], GELU_C);
                    sts32(d, c.x);
                    sts32(d + 128, c.y);
                    sts32(d + 256, c.z);
                    sts32(d + 384, c.w);
                }
            }
            asm volatile("fence.proxy.async.shared::cta;" ::: "memory");
            asm volatile("bar.sync 1, 256;" ::: "memory");
            TRS_(2);
        }

        const uint64_t w1desc = make_desc(sbase + SM_W1, W1_LBO, W1_SBO);
        const uint64_t w2desc = make_desc(sbase + SM_W2, W2_LBO, W2_SBO);
        const uint32_t ldm_addr = sbase + SM_STG + wg * STG_BYTES +
                                  (16 * warp + (lane & 7) + ((lane >> 3) & 1) * 8) * STG_PITCH + (lane >> 4) * 16;
        const uint32_t out_addr = sbase + SM_OUT + wg * OUT_BYTES + (16 * warp + (lane >> 2)) * PXB + (lane & 3) * 16;

        uint32_t a[6][4], r[6][4];
        uint32_t h[2][24], acc2[24];
        uint32_t p[24][4], u[2][4];
        uint16_t tl[2][4], tg[2][4];
        uint32_t ps[2][2], sq[4], rp[2], cp[2], st, sx;
        auto fence_regs = [&](auto& v) {
#pragma unroll
            for (int i = 0; i < (int)(sizeof(v) / 4); i++) asm volatile("" : "+r"(v[i]) :: "memory");
        };
#pragma unroll
        for (int i = 0; i < 24; i++) acc2[i] = h[0][i] = h[1][i] = 0u;
        fence_regs(acc2);
        fence_regs(h[0]);
        fence_regs(h[1]);

        auto layernorm = [&](auto Tc) {
            constexpr int t = decltype(Tc)::value;
            if constexpr (t == SG_LD || t == SG_LD + 1) {
#pragma unroll
                for (int ks = 3 * (t - SG_LD); ks < 3 * (t - SG_LD) + 3; ks++)
                    ldsm4(r[ks][0], r[ks][1], r[ks][2], r[ks][3], ldm_addr + ks * 32);
            }
            if constexpr (t == SG_SUM - 1 || t == SG_SUM) {
                constexpr int k0 = 3 * (t - SG_SUM + 1);
#pragma unroll
                for (int j = 0; j < 2; j++)
                    ps[t - SG_SUM + 1][j] = hadd2(hadd2(hadd2(r[k0][j], r[k0][j + 2]), hadd2(r[k0 + 1][j], r[k0 + 1][j + 2])),
                                                  hadd2(r[k0 + 2][j], r[k0 + 2][j + 2]));
            }
            if constexpr (t == SG_SUM) {
                st = fold(hadd2(ps[0][0], ps[1][0]), hadd2(ps[0][1], ps[1][1]));
                sx = __shfl_xor_sync(0xffffffffu, st, 1);
            }
            if constexpr (t == SG_SH2 || t == SG_VA2) {
                st = hadd2(st, sx);
                sx = __shfl_xor_sync(0xffffffffu, st, 2);
            }
            if constexpr (t == SG_CEN) {
                st = hadd2(st, sx);
                const float m0 = bf_lo(st) * (-1.0f / CH), m1 = bf_hi(st) * (-1.0f / CH);
                cp[0] = pack_bf16(m0, m0);
                cp[1] = pack_bf16(m1, m1);
            }
            if constexpr (t >= SG_CEN && t < SG_CEN + 3) {
#pragma unroll
                for (int ks = 2 * (t - SG_CEN); ks < 2 * (t - SG_CEN) + 2; ks++) {
#pragma unroll
                    for (int j = 0; j < 4; j++) {
                        r[ks][j] = hadd2(r[ks][j], cp[j & 1]);
                        sq[j] = ks == 0 ? hmul2(r[ks][j], r[ks][j]) : hfma2(r[ks][j], r[ks][j], sq[j]);
                    }
                }
            }
            if constexpr (t == SG_VAR) {
                st = fold(hadd2(sq[0], sq[2]), hadd2(sq[1], sq[3]));
                sx = __shfl_xor_sync(0xffffffffu, st, 1);
            }
            if constexpr (t == SG_RS) {
                st = hadd2(st, sx);
                float rs[2];
#pragma unroll
                for (int j = 0; j < 2; j++) {
                    constexpr float K = 1.0f / (GELU_S * GELU_S);
                    asm("rsqrt.approx.ftz.f32 %0, %1;" : "=f"(rs[j]) : "f"(fmaf(j ? bf_hi(st) : bf_lo(st), K / CH, K * 1e-5f)));
                }
#pragma unroll
                for (int j = 0; j < 2; j++) rp[j] = pack_bf16(rs[j], rs[j]);
            }
            if constexpr (t >= SG_CVT && t < SG_CVT + 3) {
#pragma unroll
                for (int ks = 2 * (t - SG_CVT); ks < 2 * (t - SG_CVT) + 2; ks++)
#pragma unroll
                    for (int j = 0; j < 4; j++) r[ks][j] = hmul2(r[ks][j], rp[j & 1]);
#pragma unroll
                for (int ks = 2 * (t - SG_CVT); ks < 2 * (t - SG_CVT) + 2; ks++)
#pragma unroll
                    for (int j = 0; j < 4; j++) a[ks][j] = pack_f16(bf_lo(r[ks][j]), bf_hi(r[ks][j]));
            }
        };
        auto gelu = [&](auto Tc) {
            constexpr int t = decltype(Tc)::value;
            constexpr int sf = (t + 1) % 24, sb = (t + 23) % 24;
            if constexpr (t >= 0) {
#pragma unroll
                for (int i = 0; i < 4; i++) gelu_tanh(tl[t & 1][i], tg[t & 1][i], u[t & 1][i]);
            }
#pragma unroll
            for (int i = 0; i < 4; i++) u[(t + 1) & 1][i] = gelu_front(h[(sf / 6) & 1][4 * (sf % 6) + i]);
            if constexpr (t >= 1) {
#pragma unroll
                for (int i = 0; i < 4; i++)
                    p[sb][i] = gelu_back(h[(sb / 6) & 1][4 * (sb % 6) + i], tl[(t + 1) & 1][i], tg[(t + 1) & 1][i]);
            }
        };
        auto arrive = [&](int bar) {
            __syncwarp();
            mbar_arrive_if(bars + 8 * (bar + wg), lane == 0);
        };
        auto store_out = [&](int i) {
            const int half = i / 3, j = i % 3;
            sts128(out_addr + half * 8 * PXB + j * 64,
                   make_uint4(h2bf(acc2[8 * j + half]), h2bf(acc2[8 * j + 2 + half]), h2bf(acc2[8 * j + 4 + half]),
                              h2bf(acc2[8 * j + 6 + half])));
        };
        auto out_ready = [&]() {
            asm volatile("fence.proxy.async.shared::cta;" ::: "memory");
            arrive(B_OUT_READY);
        };

        mbar_wait(bars + 8 * (B_STG_FULL + wg), 0);
        TRS_(3);
        static_for<SG_LD, SG_CVT + 3>(layernorm);
        SCHED_FENCE();
        arrive(B_STG_EMPTY);
        WG_FENCE();
#pragma unroll
        for (int ks = 0; ks < 6; ks++) gemm1_step(h[0], a, w1desc, 0, ks);
        WG_COMMIT();
#pragma unroll
        for (int ks = 0; ks < 6; ks++) gemm1_step(h[1], a, w1desc, 1, ks);
        WG_COMMIT();
        wg_wait<1>();
        fence_regs(h[0]);
        static_for<-1, 5>(gelu);
        wg_wait<0>();

#pragma unroll 1
        for (int it = 0;; it++) {
            bool done = false;
            static_for<5, 29>([&](auto Tc) {
                constexpr int t = decltype(Tc)::value;
                if (done) return;
                if constexpr (t == 5) {
                    wg_wait<0>();
                    fence_regs(h[0]);
                } else if constexpr (t % 6 == 5) {
                    wg_wait<1>();
                } else if constexpr (t == SG_EPI) {
                    wg_wait<2>();
                    fence_regs(acc2);
                }
                if constexpr (t % 6 == 5) fence_regs(h[((t + 1) / 6) & 1]);
                if constexpr (t == SG_LD) mbar_wait(bars + 8 * (B_STG_FULL + wg), (it + 1) & 1);
                if constexpr (t == SG_OUT) out_ready();
                if constexpr (t == SG_SUM + 1) arrive(B_STG_EMPTY);
                if constexpr (t == SG_EPI) {
                    mbar_wait(bars + 8 * (B_OUT_FREE + wg), it & 1);
                    if (it == NT / 2 - 1) { done = true; return; }
                }
                constexpr bool g1seg = t % 6 >= 1 && t % 6 <= 3;
                if constexpr (t <= 25 || g1seg) {
                    WG_FENCE();
                    if constexpr (t <= 25) {
#pragma unroll
                        for (int j = (t == 5 ? 0 : t - 2); j <= t - 2; j++) gemm2_step(acc2, p[j], w2desc, j);
                    }
                    if constexpr (g1seg) {
                        if constexpr (t == 25) WG_COMMIT();
                        constexpr int c = (t / 6 + 1) % 4;
                        gemm1_step(h[c & 1], a, w1desc, c, (t % 6 - 1) * 2);
                        gemm1_step(h[c & 1], a, w1desc, c, (t % 6 - 1) * 2 + 1);
                    }
                    WG_COMMIT();
                }
                gelu(Tc);
                if constexpr (t >= SG_EPI) {
#pragma unroll
                    for (int i = 3 * (t - SG_EPI); i < 3 * (t - SG_EPI) + 3; i++) store_out(i);
                }
                layernorm(Tc);
                SCHED_FENCE();
            });
            if (done) break;
            wg_wait<0>();
        }
        wg_wait<0>();
        fence_regs(acc2);
#pragma unroll
        for (int i = 0; i < 6; i++) store_out(i);
        out_ready();
        TRS_(4);
    }
}

typedef CUresult (*PFN_encodeTiled)(CUtensorMap*, CUtensorMapDataType, cuuint32_t, void*, const cuuint64_t*,
                                    const cuuint64_t*, const cuuint32_t*, const cuuint32_t*, CUtensorMapInterleave,
                                    CUtensorMapSwizzle, CUtensorMapL2promotion, CUtensorMapFloatOOBfill);

}

extern "C" void kernel_launch(void* const* d_in, const int* in_sizes, int n_in, void* d_out, int out_size) {
    const __nv_bfloat16* x = (const __nv_bfloat16*)d_in[0];
    const __nv_bfloat16* dwl = (const __nv_bfloat16*)d_in[1];
    const __nv_bfloat16* dws = (const __nv_bfloat16*)d_in[2];
    const __nv_bfloat16* w1 = (const __nv_bfloat16*)d_in[3];
    const __nv_bfloat16* w2 = (const __nv_bfloat16*)d_in[4];

    static PFN_encodeTiled encode = nullptr;
    if (!encode) {
        void* fn = nullptr;
        cudaDriverEntryPointQueryResult qres;
        cudaGetDriverEntryPoint("cuTensorMapEncodeTiled", &fn, cudaEnableDefault, &qres);
        encode = (PFN_encodeTiled)fn;
        cudaFuncSetAttribute(fused_block_kernel, cudaFuncAttributeMaxDynamicSharedMemorySize, SMEM_TOTAL);
    }
    CUtensorMap rowmap, tilemap, outmap;
    cuuint64_t gdim[3] = {(cuuint64_t)CH, (cuuint64_t)IMG_W, (cuuint64_t)IMG_H};
    cuuint64_t gstride[2] = {(cuuint64_t)PXB, (cuuint64_t)IMG_W * PXB};
    cuuint32_t estr[3] = {1, 1, 1};
    cuuint32_t box_row[3] = {(cuuint32_t)CH, (cuuint32_t)ROW_PX, (cuuint32_t)TR};
    cuuint32_t box_tile[3] = {(cuuint32_t)CH, (cuuint32_t)BW, (cuuint32_t)TR};
    encode(&rowmap, CU_TENSOR_MAP_DATA_TYPE_BFLOAT16, 3, (void*)x, gdim, gstride, box_row, estr,
           CU_TENSOR_MAP_INTERLEAVE_NONE, CU_TENSOR_MAP_SWIZZLE_NONE, CU_TENSOR_MAP_L2_PROMOTION_L2_256B,
           CU_TENSOR_MAP_FLOAT_OOB_FILL_NONE);
    encode(&tilemap, CU_TENSOR_MAP_DATA_TYPE_BFLOAT16, 3, (void*)x, gdim, gstride, box_tile, estr,
           CU_TENSOR_MAP_INTERLEAVE_NONE, CU_TENSOR_MAP_SWIZZLE_NONE, CU_TENSOR_MAP_L2_PROMOTION_L2_256B,
           CU_TENSOR_MAP_FLOAT_OOB_FILL_NONE);
    encode(&outmap, CU_TENSOR_MAP_DATA_TYPE_BFLOAT16, 3, d_out, gdim, gstride, box_tile, estr,
           CU_TENSOR_MAP_INTERLEAVE_NONE, CU_TENSOR_MAP_SWIZZLE_NONE, CU_TENSOR_MAP_L2_PROMOTION_NONE,
           CU_TENSOR_MAP_FLOAT_OOB_FILL_NONE);
    fused_block_kernel<<<NCTA, NTHREADS, SMEM_TOTAL>>>(rowmap, tilemap, outmap, dwl, dws, w1, w2);
}
```

```cpp
#include <cuda_runtime.h>
#include <cuda_bf16.h>
#include <cuda.h>
#include <stdint.h>
#include <type_traits>

#define TRS_(i)
#define PTR_(k)

namespace {

constexpr int IMG_H = 512, IMG_W = 512, CH = 96, HID = 384;
constexpr int BW = 16;
constexpr int TR = 4;
constexpr int NT = 32;
constexpr int NCTA = (IMG_W / BW) * (IMG_H / (TR * NT));
constexpr int PXB = CH * 2;
constexpr int ROW_PX = BW + 4;
constexpr int ROW_BYTES = ROW_PX * PXB;
constexpr int UNIT_BYTES = TR * ROW_BYTES;
constexpr int STG_PITCH = 208;
constexpr int STG_BYTES = 64 * STG_PITCH;
constexpr int OUT_BYTES = 64 * PXB;
constexpr int NTHREADS = 512;
constexpr int MLP_REGS = 168, TMA_REGS = 24, CONV_REGS = 512 - 2 * MLP_REGS - TMA_REGS;

constexpr int W1_BYTES = CH * HID * 2;
constexpr int W2_BYTES = HID * CH * 2;
constexpr int WPIECE = 24576;
constexpr int SM_W1 = 0;
constexpr int SM_W2 = SM_W1 + W1_BYTES;
constexpr int SM_RING = SM_W2 + W2_BYTES;
constexpr int SM_OUT = SM_RING + 2 * UNIT_BYTES;
constexpr int SM_STG = SM_OUT + 2 * OUT_BYTES;
constexpr int SM_BAR = SM_STG + 2 * STG_BYTES;
constexpr int SMEM_TOTAL = SM_BAR + 256;
static_assert(SMEM_TOTAL <= 232448, "smem");

constexpr int B_RING_FULL = 0;
constexpr int B_RING_EMPTY = 2;
constexpr int B_STG_FULL = 4;
constexpr int B_STG_EMPTY = 6;
constexpr int B_X_FULL = 8;
constexpr int B_OUT_READY = 10;
constexpr int B_OUT_FREE = 12;
constexpr int B_FILTER = 14;
constexpr int B_WEIGHTS = 16;

constexpr int W1_LBO = 8 * HID * 2, W1_SBO = 128;
constexpr int W2_KG = 8 * CH * 2;
constexpr int W2_LBO = 8 * W2_KG, W2_SBO = 128;

constexpr float GELU_S = 0.3292034911525734f;
constexpr uint32_t GELU_CH2 = 0x3FC23FC2u, GELU_CL2 = 0x3B513B51u;
constexpr uint32_t GELU_A2 = 0x40D940D9u;

__device__ __forceinline__ uint32_t smem_u32(const void* p) {
    return (uint32_t)__cvta_generic_to_shared(p);
}
__device__ __forceinline__ uint64_t make_desc(uint32_t addr, uint32_t lbo, uint32_t sbo) {
    return (uint64_t)((addr & 0x3FFFF) >> 4) | ((uint64_t)(lbo >> 4) << 16) | ((uint64_t)(sbo >> 4) << 32);
}
__device__ __forceinline__ void mbar_init(uint32_t bar, uint32_t cnt) {
    asm volatile("mbarrier.init.shared::cta.b64 [%0], %1;" ::"r"(bar), "r"(cnt));
}
__device__ __forceinline__ void mbar_expect_tx(uint32_t bar, uint32_t bytes) {
    asm volatile("mbarrier.arrive.expect_tx.shared::cta.b64 _, [%0], %1;" ::"r"(bar), "r"(bytes) : "memory");
}
__device__ __forceinline__ void mbar_arrive_if(uint32_t bar, bool pred) {
    asm volatile("{\n.reg .pred p;\nsetp.ne.u32 p, %1, 0;\n@p mbarrier.arrive.shared::cta.b64 _, [%0];\n}\n"
                 ::"r"(bar), "r"((uint32_t)pred) : "memory");
}
__device__ __forceinline__ void mbar_wait(uint32_t bar, uint32_t parity) {
    asm volatile(
        "{\n"
        ".reg .pred p;\n"
        "WAIT_LOOP:\n"
        "mbarrier.try_wait.parity.shared::cta.b64 p, [%0], %1, %2;\n"
        "@p bra WAIT_DONE;\n"
        "bra WAIT_LOOP;\n"
        "WAIT_DONE:\n"
        "}\n" ::"r"(bar), "r"(parity), "r"(20000) : "memory");
}
__device__ __forceinline__ void tma_load3d(uint32_t dst, const CUtensorMap* map, int cx, int cy, uint32_t bar) {
    asm volatile(
        "cp.async.bulk.tensor.3d.shared::cluster.global.mbarrier::complete_tx::bytes [%0], [%1, {%2, %3, %4}], [%5];"
        ::"r"(dst), "l"((uint64_t)map), "r"(0), "r"(cx), "r"(cy), "r"(bar) : "memory");
}
__device__ __forceinline__ void bulk_load(uint32_t dst, const void* src, uint32_t bytes, uint32_t bar) {
    asm volatile("cp.async.bulk.shared::cluster.global.mbarrier::complete_tx::bytes [%0], [%1], %2, [%3];"
                 ::"r"(dst), "l"(src), "r"(bytes), "r"(bar) : "memory");
}
__device__ __forceinline__ uint4 lds128(uint32_t addr) {
    uint4 v;
    asm volatile("ld.shared.v4.u32 {%0,%1,%2,%3}, [%4];" : "=r"(v.x), "=r"(v.y), "=r"(v.z), "=r"(v.w) : "r"(addr));
    return v;
}
__device__ __forceinline__ uint32_t lds32(uint32_t addr) {
    uint32_t v;
    asm volatile("ld.shared.u32 %0, [%1];" : "=r"(v) : "r"(addr));
    return v;
}
__device__ __forceinline__ void sts128(uint32_t addr, uint4 v) {
    asm volatile("st.shared.v4.u32 [%0], {%1,%2,%3,%4};" ::"r"(addr), "r"(v.x), "r"(v.y), "r"(v.z), "r"(v.w) : "memory");
}
__device__ __forceinline__ void sts32(uint32_t addr, uint32_t a) {
    asm volatile("st.shared.u32 [%0], %1;" ::"r"(addr), "r"(a) : "memory");
}
__device__ __forceinline__ void ldsm4(uint32_t& a, uint32_t& b, uint32_t& c, uint32_t& d, uint32_t addr) {
    asm volatile("ldmatrix.sync.aligned.m8n8.x4.shared.b16 {%0,%1,%2,%3}, [%4];"
                 : "=r"(a), "=r"(b), "=r"(c), "=r"(d) : "r"(addr));
}
__device__ __forceinline__ void ldsm2(uint32_t& a, uint32_t& b, uint32_t addr) {
    asm volatile("ldmatrix.sync.aligned.m8n8.x2.shared.b16 {%0,%1}, [%2];" : "=r"(a), "=r"(b) : "r"(addr));
}
__device__ __forceinline__ void stsm4(uint32_t addr, uint32_t a, uint32_t b, uint32_t c, uint32_t d) {
    asm volatile("stmatrix.sync.aligned.m8n8.x4.shared.b16 [%0], {%1,%2,%3,%4};"
                 ::"r"(addr), "r"(a), "r"(b), "r"(c), "r"(d) : "memory");
}
__device__ __forceinline__ void stsm2(uint32_t addr, uint32_t a, uint32_t b) {
    asm volatile("stmatrix.sync.aligned.m8n8.x2.shared.b16 [%0], {%1,%2};" ::"r"(addr), "r"(a), "r"(b) : "memory");
}
__device__ __forceinline__ uint32_t hfma2(uint32_t a, uint32_t b, uint32_t c) {
    uint32_t d;
    asm("fma.rn.bf16x2 %0, %1, %2, %3;" : "=r"(d) : "r"(a), "r"(b), "r"(c));
    return d;
}
__device__ __forceinline__ uint32_t hmul2(uint32_t a, uint32_t b) {
    uint32_t d;
    asm("mul.rn.bf16x2 %0, %1, %2;" : "=r"(d) : "r"(a), "r"(b));
    return d;
}
__device__ __forceinline__ uint32_t hadd2(uint32_t a, uint32_t b) {
    uint32_t d;
    asm("add.rn.bf16x2 %0, %1, %2;" : "=r"(d) : "r"(a), "r"(b));
    return d;
}
__device__ __forceinline__ uint32_t hsub2(uint32_t a, uint32_t b) {
    uint32_t d;
    asm("sub.rn.bf16x2 %0, %1, %2;" : "=r"(d) : "r"(a), "r"(b));
    return d;
}
__device__ __forceinline__ uint32_t fold(uint32_t a, uint32_t b) {
    return hadd2(__byte_perm(a, b, 0x5410), __byte_perm(a, b, 0x7632));
}
__device__ __forceinline__ float bf_lo(uint32_t v) { return __uint_as_float(v << 16); }
__device__ __forceinline__ float bf_hi(uint32_t v) { return __uint_as_float(v & 0xffff0000u); }
__device__ __forceinline__ uint32_t pack_bf16(float lo, float hi) {
    uint32_t d;
    asm("cvt.rn.bf16x2.f32 %0, %1, %2;" : "=r"(d) : "f"(hi), "f"(lo));
    return d;
}
__device__ __forceinline__ uint32_t pack_f16(float lo, float hi) {
    uint32_t d;
    asm("cvt.rn.f16x2.f32 %0, %1, %2;" : "=r"(d) : "f"(hi), "f"(lo));
    return d;
}
__device__ __forceinline__ uint32_t bf2h(uint32_t v) { return pack_f16(bf_lo(v), bf_hi(v)); }
__device__ __forceinline__ uint4 bf2h4(uint4 v) { return make_uint4(bf2h(v.x), bf2h(v.y), bf2h(v.z), bf2h(v.w)); }
__device__ __forceinline__ uint32_t mulc(uint32_t v) { return hfma2(v, GELU_CH2, hmul2(v, GELU_CL2)); }
__device__ __forceinline__ uint32_t h2bf(uint32_t h) {
    float lo, hi;
    asm("{\n.reg .b16 l, h;\nmov.b32 {l, h}, %2;\ncvt.f32.f16 %0, l;\ncvt.f32.f16 %1, h;\n}\n" : "=f"(lo), "=f"(hi) : "r"(h));
    return pack_bf16(lo, hi);
}

#define WG_FENCE() asm volatile("wgmma.fence.sync.aligned;" ::: "memory")
#define WG_COMMIT() asm volatile("wgmma.commit_group.sync.aligned;" ::: "memory")
template <int N>
__device__ __forceinline__ void wg_wait() {
    asm volatile("wgmma.wait_group.sync.aligned %0;" ::"n"(N) : "memory");
}
#define SCHED_FENCE() asm volatile("pmevent.mask 0;" ::: "memory")

template <bool ACC>
__device__ __forceinline__ void wgmma_rs(uint32_t (&d)[24], const uint32_t (&a)[4], uint64_t desc) {
    asm volatile(
        "{\n"
        ".reg .pred p;\n"
        "setp.ne.b32 p, %29, 0;\n"
        "wgmma.mma_async.sync.aligned.m64n96k16.f16.f16.f16 {"
        "%0,%1,%2,%3,%4,%5,%6,%7,%8,%9,%10,%11,%12,%13,%14,%15,"
        "%16,%17,%18,%19,%20,%21,%22,%23"
        "}, {%24,%25,%26,%27}, %28, p, 1, 1, 1;\n"
        "}\n"
        : "+r"(d[0]), "+r"(d[1]), "+r"(d[2]), "+r"(d[3]), "+r"(d[4]), "+r"(d[5]), "+r"(d[6]), "+r"(d[7]),
          "+r"(d[8]), "+r"(d[9]), "+r"(d[10]), "+r"(d[11]), "+r"(d[12]), "+r"(d[13]), "+r"(d[14]), "+r"(d[15]),
          "+r"(d[16]), "+r"(d[17]), "+r"(d[18]), "+r"(d[19]), "+r"(d[20]), "+r"(d[21]), "+r"(d[22]), "+r"(d[23])
        : "r"(a[0]), "r"(a[1]), "r"(a[2]), "r"(a[3]), "l"(desc), "n"(ACC ? 1 : 0));
}
__device__ __forceinline__ void gemm1_step(uint32_t (&h)[24], const uint32_t (&a)[6][4], uint64_t w1desc, int c, int ks) {
    const uint64_t d = w1desc + (uint64_t)((c * 12 * W1_SBO + ks * 2 * W1_LBO) >> 4);
    if (ks == 0) wgmma_rs<false>(h, a[0], d);
    else wgmma_rs<true>(h, a[ks], d);
}
__device__ __forceinline__ void gemm2_step(uint32_t (&acc2)[24], const uint32_t (&p)[4], uint64_t w2desc, int j) {
    const uint64_t d = w2desc + (uint64_t)(((16 * (j % 3) + j / 3) * W2_KG) >> 4);
    if (j == 0) wgmma_rs<false>(acc2, p, d);
    else wgmma_rs<true>(acc2, p, d);
}
__device__ __forceinline__ uint32_t gelu_front(uint32_t y) {
    uint32_t t, u;
    asm("fma.rn.f16x2 %0, %1, %1, %2;" : "=r"(t) : "r"(y), "r"(GELU_A2));
    asm("mul.rn.f16x2 %0, %1, %2;" : "=r"(u) : "r"(y), "r"(t));
    return u;
}
__device__ __forceinline__ void gelu_tanh(uint16_t& lo, uint16_t& hi, uint32_t u) {
    asm("{\n.reg .b16 l, h;\nmov.b32 {l, h}, %2;\ntanh.approx.f16 %0, l;\ntanh.approx.f16 %1, h;\n}\n"
        : "=h"(lo), "=h"(hi) : "r"(u));
}
__device__ __forceinline__ uint32_t gelu_back(uint32_t y, uint16_t lo, uint16_t hi) {
    uint32_t g;
    asm("{\n.reg .b32 t;\nmov.b32 t, {%2, %3};\nfma.rn.f16x2 %0, %1, t, %1;\n}\n" : "=r"(g) : "r"(y), "h"(lo), "h"(hi));
    return g;
}

template <int B, int E, typename F>
__device__ __forceinline__ void static_for(F&& f) {
    if constexpr (B < E) {
        f(std::integral_constant<int, B>{});
        static_for<B + 1, E>(f);
    }
}

template <int NP, int R0>
__device__ __forceinline__ void conv_row(uint32_t (&o)[2 * NP], uint32_t (&acc)[4][NP][3], const uint32_t (&w)[5][7],
                                         const uint32_t (&x)[2 * NP + 4]) {
    uint32_t e[NP + 1], f[NP + 1], t[5][NP][3];
#pragma unroll
    for (int i = 0; i <= NP; i++) {
        e[i] = hsub2(x[2 * i], x[2 * i + 1]);
        f[i] = hsub2(x[2 * i + 2], x[2 * i + 1]);
    }
#pragma unroll
    for (int p = 0; p < NP; p++) {
#pragma unroll
        for (int r = R0; r < 5; r++) {
            const uint32_t(&h)[7] = w[4 - r];
            t[r][p][1] = r < 4 ? hfma2(x[2 * p + 1], h[3], acc[r & 3][p][1]) : hmul2(x[2 * p + 1], h[3]);
            t[r][p][0] = r < 4 ? hfma2(x[2 * p + 4], h[2], acc[r & 3][p][0]) : hmul2(x[2 * p + 4], h[2]);
            t[r][p][2] = r < 4 ? hfma2(x[2 * p + 5], h[2], acc[r & 3][p][2]) : hmul2(x[2 * p + 5], h[2]);
        }
#pragma unroll
        for (int r = R0; r < 5; r++) {
            const uint32_t(&h)[7] = w[4 - r];
            t[r][p][1] = hfma2(x[2 * p + 3], h[4], t[r][p][1]);
            t[r][p][0] = hfma2(e[p], h[0], t[r][p][0]);
            t[r][p][2] = hfma2(f[p], h[5], t[r][p][2]);
        }
#pragma unroll
        for (int r = R0; r < 5; r++) {
            const uint32_t(&h)[7] = w[4 - r];
            t[r][p][0] = hfma2(e[p + 1], h[1], t[r][p][0]);
            t[r][p][2] = hfma2(f[p + 1], h[6], t[r][p][2]);
        }
        if (R0 == 0) {
            o[2 * p] = hadd2(t[0][p][0], t[0][p][1]);
            o[2 * p + 1] = hadd2(t[0][p][1], t[0][p][2]);
        }
#pragma unroll
        for (int r = (R0 > 0 ? R0 : 1); r < 5; r++)
#pragma unroll
            for (int m = 0; m < 3; m++) acc[r - 1][p][m] = t[r][p][m];
    }
}

constexpr int SG_LD = 9, SG_SUM = 11, SG_SH2 = 12, SG_CEN = 13, SG_VAR = 15, SG_VA2 = 16, SG_RS = 17, SG_CVT = 18;
constexpr int SG_OUT = 7;
constexpr int SG_EPI = 27;

__global__ void __launch_bounds__(NTHREADS, 1)
fused_block_kernel(const __grid_constant__ CUtensorMap rowmap, const __grid_constant__ CUtensorMap tilemap,
                   const __grid_constant__ CUtensorMap outmap,
                   const __nv_bfloat16* __restrict__ dwl, const __nv_bfloat16* __restrict__ dws,
                   const __nv_bfloat16* __restrict__ w1, const __nv_bfloat16* __restrict__ w2) {
    extern __shared__ __align__(1024) uint8_t smem[];
    const uint32_t sbase = smem_u32(smem);
    const int tid = threadIdx.x;
    const int wid = __shfl_sync(0xffffffffu, tid >> 5, 0);
    const int wg = wid >> 2, warp = wid & 3;
    const int lane = tid & 31;
    const uint32_t bars = sbase + SM_BAR;
    const int x0 = (blockIdx.x >> 2) * BW, y0 = (blockIdx.x & 3) * (TR * NT);

    if (tid == NTHREADS - 128) {
        const char* w1b = reinterpret_cast<const char*>(w1);
        const char* w2b = reinterpret_cast<const char*>(w2);
        asm volatile("cp.async.bulk.prefetch.L2.global [%0], %1;"
                     ::"l"(((blockIdx.x & 1) ? w2b : w1b) + (blockIdx.x >> 1) * (W1_BYTES / (NCTA / 2))), "r"(W1_BYTES / (NCTA / 2))
                     : "memory");
        mbar_init(bars + 8 * B_FILTER, 1);
        mbar_init(bars + 8 * B_RING_FULL, 1);
        mbar_init(bars + 8 * B_RING_FULL + 8, 1);
#pragma unroll
        for (int i = 0; i < 6; i++) mbar_init(bars + 8 * (B_WEIGHTS + i), 1);
        asm volatile("fence.mbarrier_init.release.cluster;" ::: "memory");
        mbar_expect_tx(bars + 8 * B_FILTER, 34 * PXB);
        bulk_load(sbase + SM_OUT, dws, 25 * PXB, bars + 8 * B_FILTER);
        bulk_load(sbase + SM_OUT + 25 * PXB, dwl, 9 * PXB, bars + 8 * B_FILTER);
#pragma unroll
        for (int i = 0; i < 6; i++) {
            if (i < 2) {
                mbar_expect_tx(bars + 8 * (B_RING_FULL + i), UNIT_BYTES);
                tma_load3d(sbase + SM_RING + i * UNIT_BYTES, &rowmap, x0 - 2, y0 - 2 + TR * i, bars + 8 * (B_RING_FULL + i));
            }
            mbar_expect_tx(bars + 8 * (B_WEIGHTS + i), WPIECE);
            bulk_load(sbase + i * WPIECE, (i < 3 ? w1b : w2b) + (i % 3) * WPIECE, WPIECE, bars + 8 * (B_WEIGHTS + i));
        }
    } else if (tid == NTHREADS - 96) {
#pragma unroll
        for (int m = 0; m < 2; m++) {
            mbar_init(bars + 8 * (B_RING_EMPTY + m), 4);
            mbar_init(bars + 8 * (B_STG_FULL + m), 4);
            mbar_init(bars + 8 * (B_STG_EMPTY + m), 4);
                        mbar_init(bars + 8 * (B_X_FULL + m), 1);
            mbar_init(bars + 8 * (B_OUT_READY + m), 4);
            mbar_init(bars + 8 * (B_OUT_FREE + m), 1);
        }
        asm volatile("fence.mbarrier_init.release.cluster;" ::: "memory");
    }
    __syncthreads();

    if (wg == 3) {
        asm volatile("setmaxnreg.dec.sync.aligned.u32 %0;" ::"n"(TMA_REGS));
        const int m = warp >> 1;
        if (lane == 0) {
            if (warp == 0 || warp == 3) {
                const uint32_t fb = bars + 8 * (B_RING_FULL + m);
#pragma unroll 1
                for (int j = m + 2; j <= NT; j += 2) {
                    mbar_wait(bars + 8 * (B_RING_EMPTY + m), ((j >> 1) & 1) ^ 1);
                    mbar_expect_tx(fb, UNIT_BYTES);
                    tma_load3d(sbase + SM_RING + m * UNIT_BYTES, &rowmap, x0 - 2, y0 - 2 + TR * j, fb);
                }
                if (m == 1) {
                    mbar_wait(bars + 8 * (B_RING_EMPTY + m), ((NT >> 1) & 1) ^ 1);
                    mbar_arrive_if(fb, true);
                }
            } else {
                const uint32_t fb = bars + 8 * (B_X_FULL + m), buf = sbase + SM_OUT + m * OUT_BYTES;
                mbar_wait(bars + 8 * (B_OUT_READY + m), 0);
#pragma unroll 1
                for (int i = 0; i < NT / 2; i++) {
                    const int cy = y0 + TR * (2 * i + m);
                    PTR_(0);
                    mbar_expect_tx(fb, OUT_BYTES);
                    tma_load3d(buf, &tilemap, x0, cy, fb);
                    mbar_wait(fb, i & 1);
                    PTR_(1);
                    asm volatile("cp.async.bulk.tensor.3d.global.shared::cta.bulk_group [%0, {%1, %2, %3}], [%4];"
                                 ::"l"((uint64_t)&outmap), "r"(0), "r"(x0), "r"(cy), "r"(buf) : "memory");
                    asm volatile("cp.async.bulk.commit_group;" ::: "memory");
                    asm volatile("cp.async.bulk.wait_group 0;" ::: "memory");
                    PTR_(2);
                    mbar_arrive_if(bars + 8 * (B_OUT_FREE + m), true);
                    mbar_wait(bars + 8 * (B_OUT_READY + m), (i & 1) ^ 1);
                    PTR_(3);
                    asm volatile("cp.reduce.async.bulk.tensor.3d.global.shared::cta.add.bulk_group [%0, {%1, %2, %3}], [%4];"
                                 ::"l"((uint64_t)&outmap), "r"(0), "r"(x0), "r"(cy), "r"(buf) : "memory");
                    asm volatile("cp.async.bulk.commit_group;" ::: "memory");
                    asm volatile("cp.async.bulk.wait_group 0;" ::: "memory");
                    PTR_(4);
                }
            }
        }
    } else if (wg == 2) {
        asm volatile("setmaxnreg.inc.sync.aligned.u32 %0;" ::"n"(CONV_REGS));
        uint32_t wa[5][7], wb[5][7];
        {
            const uint32_t pa = sbase + SM_OUT + 4 * lane, pb = sbase + SM_OUT + 4 * (32 + (lane & 15));
            const bool mir = lane >= 16;
            mbar_wait(bars + 8 * B_FILTER, 0);
#pragma unroll
            for (int r = 0; r < 5; r++) {
                uint32_t u[5], v[5];
#pragma unroll
                for (int c = 0; c < 5; c++) {
                    u[c] = lds32(pa + (5 * r + c) * PXB);
                    v[c] = lds32(pb + (5 * r + c) * PXB);
                    if (r >= 1 && r <= 3 && c >= 1 && c <= 3) {
                        u[c] = hadd2(u[c], lds32(pa + (25 + 3 * (r - 1) + c - 1) * PXB));
                        v[c] = hadd2(v[c], lds32(pb + (25 + 3 * (r - 1) + c - 1) * PXB));
                    }
                }
#pragma unroll
                for (int c = 0; c < 2; c++) {
                    const uint32_t lo = v[c], hi = v[4 - c];
                    v[c] = mir ? hi : lo;
                    v[4 - c] = mir ? lo : hi;
                }
                wa[r][0] = u[0]; wa[r][1] = u[2]; wa[r][2] = u[4]; wa[r][3] = hadd2(u[0], u[1]);
                wa[r][4] = hadd2(u[2], u[3]); wa[r][5] = u[1]; wa[r][6] = u[3];
                wb[r][0] = v[0]; wb[r][1] = v[2]; wb[r][2] = v[4]; wb[r][3] = hadd2(v[0], v[1]);
                wb[r][4] = hadd2(v[2], v[3]); wb[r][5] = v[1]; wb[r][6] = v[3];
            }
        }
        const int mi = lane >> 3, mr = lane & 7, up = mr >> 2;
        const uint32_t ring_a = sbase + SM_RING + (4 * warp + mi) * PXB + mr * 16;
        const uint32_t ring_b0 = sbase + SM_RING + (4 * warp + (up ? 7 - mi : mi)) * PXB + 128 + (mr & 3) * 16;
        const uint32_t ring_b1 = sbase + SM_RING + (4 * warp + (up ? 3 - mi : 4 + mi)) * PXB + 128 + (mr & 3) * 16;
        const uint32_t stg_a = sbase + SM_STG + (4 * warp + mi) * STG_PITCH + mr * 16;
        const uint32_t stg_b = sbase + SM_STG + (4 * warp + (up ? 3 - mi : mi)) * STG_PITCH + 128 + (mr & 3) * 16;
        uint32_t acca[4][2][3], accb[4][1][3], xa[8], xb[6], oa[4], ob[2];
        auto fetch_a = [&](uint32_t off) {
            ldsm4(xa[0], xa[1], xa[2], xa[3], ring_a + off);
            ldsm4(xa[4], xa[5], xa[6], xa[7], ring_a + off + 4 * PXB);
        };
        auto fetch_b = [&](uint32_t off) {
            ldsm4(xb[0], xb[1], xb[2], xb[3], ring_b0 + off);
            ldsm2(xb[4], xb[5], ring_b1 + off);
        };
        const uint32_t arr = bars + 8 * (lane == 0 ? B_RING_EMPTY + 1 : B_STG_FULL);
        TRS_(0);
        mbar_wait(bars + 8 * B_RING_FULL, 0);
        TRS_(1);
        static_for<0, 4>([&](auto Rc) {
            constexpr int R = decltype(Rc)::value;
            fetch_a(R * ROW_BYTES);
            fetch_b(R * ROW_BYTES);
            conv_row<2, 4 - R>(oa, acca, wa, xa);
            conv_row<1, 4 - R>(ob, accb, wb, xb);
        });
        SCHED_FENCE();
        __syncwarp();
        mbar_arrive_if(bars + 8 * B_RING_EMPTY, lane == 0);
        mbar_wait(bars + 8 * (B_RING_FULL + 1), 0);
        fetch_a(UNIT_BYTES);
        fetch_b(UNIT_BYTES);
        TRS_(5);
#pragma unroll 1
        for (int k0 = 0; k0 < NT; k0 += 2) {
#pragma unroll
            for (int kk = 0; kk < 2; kk++) {
                const uint32_t s = kk, ph = ((k0 >> 1) & 1) ^ 1;
                const uint32_t nxt = s * UNIT_BYTES, cur = nxt ^ UNIT_BYTES, dst = s * STG_BYTES;
#pragma unroll
                for (int R = 0; R < 4; R++) {
                    conv_row<2, 0>(oa, acca, wa, xa);
                    if (R == 0) mbar_wait(bars + 8 * B_STG_EMPTY + 8 * s, ph);
                    if (R == 3) mbar_wait(bars + 8 * B_RING_FULL + 8 * s, ph);
                    fetch_a(R < 3 ? cur + (R + 1) * ROW_BYTES : nxt);
                    stsm4(stg_a + dst + R * (BW * STG_PITCH), oa[0], oa[1], oa[2], oa[3]);
                    conv_row<1, 0>(ob, accb, wb, xb);
                    fetch_b(R < 3 ? cur + (R + 1) * ROW_BYTES : nxt);
                    stsm2(stg_b + dst + R * (BW * STG_PITCH), ob[0], ob[1]);
                    if (R == 3) {
                        __syncwarp();
                        mbar_arrive_if(arr ^ (8 * s), lane < 2);
                    }
                    if (R < 3 || kk == 0) SCHED_FENCE();
                }
            }
        }
#pragma unroll
        for (int s = 0; s < 2; s++) {
            mbar_wait(bars + 8 * B_STG_EMPTY + 8 * s, 1);
            mbar_arrive_if(bars + 8 * B_STG_FULL + 8 * s, lane == 0);
        }
        TRS_(4);
    } else {
        asm volatile("setmaxnreg.inc.sync.aligned.u32 %0;" ::"n"(MLP_REGS));
        TRS_(0);
        {
            const int kk = lane & 7, a0 = (kk + (lane >> 3)) & 7;
#pragma unroll 1
            for (int t = wid; t < 24; t += 8) {
                const uint32_t base = sbase + SM_W1 + (t >> 1) * W1_LBO + (t & 1) * 384;
                uint4 v[6];
                mbar_wait(bars + 8 * (B_WEIGHTS + (t >> 3)), 0);
#pragma unroll
                for (int i = 0; i < 6; i++) v[i] = lds128(base + (i >> 1) * 128 + kk * (HID * 2) + (a0 ^ ((i & 1) * 4)) * 16);
                __syncwarp();
#pragma unroll
                for (int i = 0; i < 6; i++)
                    sts128(base + (i >> 1) * 128 + (a0 ^ ((i & 1) * 4)) * (HID * 2) + kk * 16, bf2h4(v[i]));
            }
            TRS_(1);
            const int q2 = lane & 3, k2 = lane >> 2;
#pragma unroll 1
            for (int t = wid; t < 48; t += 8) {
                const uint32_t base = sbase + SM_W2 + t * W2_KG;
                uint4 v[3];
                mbar_wait(bars + 8 * (B_WEIGHTS + 3 + (t >> 4)), 0);
#pragma unroll
                for (int i = 0; i < 3; i++) v[i] = lds128(base + k2 * (CH * 2) + i * 64 + q2 * 16);
                __syncwarp();
#pragma unroll
                for (int i = 0; i < 3; i++) {
                    const uint32_t d = base + i * 512 + k2 * 16 + q2 * 4;
                    const uint4 c = bf2h4(make_uint4(mulc(v[i].x), mulc(v[i].y), mulc(v[i].z), mulc(v[i].w)));
                    sts32(d, c.x);
                    sts32(d + 128, c.y);
                    sts32(d + 256, c.z);
                    sts32(d + 384, c.w);
                }
            }
            asm volatile("fence.proxy.async.shared::cta;" ::: "memory");
            asm volatile("bar.sync 1, 256;" ::: "memory");
            TRS_(2);
        }

        const uint64_t w1desc = make_desc(sbase + SM_W1, W1_LBO, W1_SBO);
        const uint64_t w2desc = make_desc(sbase + SM_W2, W2_LBO, W2_SBO);
        const uint32_t ldm_addr = sbase + SM_STG + wg * STG_BYTES +
                                  (16 * warp + (lane & 7) + ((lane >> 3) & 1) * 8) * STG_PITCH + (lane >> 4) * 16;
        const uint32_t out_addr = sbase + SM_OUT + wg * OUT_BYTES + (16 * warp + (lane >> 2)) * PXB + (lane & 3) * 16;

        uint32_t a[6][4], r[6][4];
        uint32_t h[2][24], acc2[24];
        uint32_t p[24][4], u[2][4];
        uint16_t tl[2][4], tg[2][4];
        uint32_t ps[2][2], sq[4], rp[2], cp[2], st, sx;
        auto fence_regs = [&](auto& v) {
#pragma unroll
            for (int i = 0; i < (int)(sizeof(v) / 4); i++) asm volatile("" : "+r"(v[i]) :: "memory");
        };
#pragma unroll
        for (int i = 0; i < 24; i++) acc2[i] = h[0][i] = h[1][i] = 0u;
        fence_regs(acc2);
        fence_regs(h[0]);
        fence_regs(h[1]);

        auto layernorm = [&](auto Tc) {
            constexpr int t = decltype(Tc)::value;
            if constexpr (t == SG_LD || t == SG_LD + 1) {
#pragma unroll
                for (int ks = 3 * (t - SG_LD); ks < 3 * (t - SG_LD) + 3; ks++)
                    ldsm4(r[ks][0], r[ks][1], r[ks][2], r[ks][3], ldm_addr + ks * 32);
            }
            if constexpr (t == SG_SUM - 1 || t == SG_SUM) {
                constexpr int k0 = 3 * (t - SG_SUM + 1);
#pragma unroll
                for (int j = 0; j < 2; j++)
                    ps[t - SG_SUM + 1][j] = hadd2(hadd2(hadd2(r[k0][j], r[k0][j + 2]), hadd2(r[k0 + 1][j], r[k0 + 1][j + 2])),
                                                  hadd2(r[k0 + 2][j], r[k0 + 2][j + 2]));
            }
            if constexpr (t == SG_SUM) {
                st = fold(hadd2(ps[0][0], ps[1][0]), hadd2(ps[0][1], ps[1][1]));
                sx = __shfl_xor_sync(0xffffffffu, st, 1);
            }
            if constexpr (t == SG_SH2 || t == SG_VA2) {
                st = hadd2(st, sx);
                sx = __shfl_xor_sync(0xffffffffu, st, 2);
            }
            if constexpr (t == SG_CEN) {
                st = hadd2(st, sx);
                const float m0 = bf_lo(st) * (-1.0f / CH), m1 = bf_hi(st) * (-1.0f / CH);
                cp[0] = pack_bf16(m0, m0);
                cp[1] = pack_bf16(m1, m1);
            }
            if constexpr (t >= SG_CEN && t < SG_CEN + 3) {
#pragma unroll
                for (int ks = 2 * (t - SG_CEN); ks < 2 * (t - SG_CEN) + 2; ks++) {
#pragma unroll
                    for (int j = 0; j < 4; j++) {
                        r[ks][j] = hadd2(r[ks][j], cp[j & 1]);
                        sq[j] = ks == 0 ? hmul2(r[ks][j], r[ks][j]) : hfma2(r[ks][j], r[ks][j], sq[j]);
                    }
                }
            }
            if constexpr (t == SG_VAR) {
                st = fold(hadd2(sq[0], sq[2]), hadd2(sq[1], sq[3]));
                sx = __shfl_xor_sync(0xffffffffu, st, 1);
            }
            if constexpr (t == SG_RS) {
                st = hadd2(st, sx);
                float rs[2];
#pragma unroll
                for (int j = 0; j < 2; j++) {
                    constexpr float K = 1.0f / (GELU_S * GELU_S);
                    asm("rsqrt.approx.ftz.f32 %0, %1;" : "=f"(rs[j]) : "f"(fmaf(j ? bf_hi(st) : bf_lo(st), K / CH, K * 1e-5f)));
                }
#pragma unroll
                for (int j = 0; j < 2; j++) rp[j] = pack_bf16(rs[j], rs[j]);
            }
            if constexpr (t >= SG_CVT && t < SG_CVT + 3) {
#pragma unroll
                for (int ks = 2 * (t - SG_CVT); ks < 2 * (t - SG_CVT) + 2; ks++)
#pragma unroll
                    for (int j = 0; j < 4; j++) r[ks][j] = hmul2(r[ks][j], rp[j & 1]);
#pragma unroll
                for (int ks = 2 * (t - SG_CVT); ks < 2 * (t - SG_CVT) + 2; ks++)
#pragma unroll
                    for (int j = 0; j < 4; j++) a[ks][j] = bf2h(r[ks][j]);
            }
        };
        auto gelu = [&](auto Tc) {
            constexpr int t = decltype(Tc)::value;
            constexpr int sf = (t + 1) % 24, sb = (t + 23) % 24;
            if constexpr (t >= 0) {
#pragma unroll
                for (int i = 0; i < 4; i++) gelu_tanh(tl[t & 1][i], tg[t & 1][i], u[t & 1][i]);
            }
#pragma unroll
            for (int i = 0; i < 4; i++) u[(t + 1) & 1][i] = gelu_front(h[(sf / 6) & 1][4 * (sf % 6) + i]);
            if constexpr (t >= 1) {
#pragma unroll
                for (int i = 0; i < 4; i++)
                    p[sb][i] = gelu_back(h[(sb / 6) & 1][4 * (sb % 6) + i], tl[(t + 1) & 1][i], tg[(t + 1) & 1][i]);
            }
        };
        auto arrive = [&](int bar) {
            __syncwarp();
            mbar_arrive_if(bars + 8 * (bar + wg), lane == 0);
        };
        auto store_out = [&](int i) {
            const int half = i / 3, j = i % 3;
            sts128(out_addr + half * 8 * PXB + j * 64,
                   make_uint4(h2bf(acc2[8 * j + half]), h2bf(acc2[8 * j + 2 + half]), h2bf(acc2[8 * j + 4 + half]),
                              h2bf(acc2[8 * j + 6 + half])));
        };
        auto out_ready = [&]() {
            asm volatile("fence.proxy.async.shared::cta;" ::: "memory");
            arrive(B_OUT_READY);
        };

        mbar_wait(bars + 8 * (B_STG_FULL + wg), 0);
        TRS_(3);
        static_for<SG_LD, SG_CVT + 3>(layernorm);
        SCHED_FENCE();
        arrive(B_STG_EMPTY);
        WG_FENCE();
#pragma unroll
        for (int ks = 0; ks < 6; ks++) gemm1_step(h[0], a, w1desc, 0, ks);
        WG_COMMIT();
#pragma unroll
        for (int ks = 0; ks < 6; ks++) gemm1_step(h[1], a, w1desc, 1, ks);
        WG_COMMIT();
        wg_wait<1>();
        fence_regs(h[0]);
        static_for<-1, 5>(gelu);
        wg_wait<0>();

#pragma unroll 1
        for (int it = 0;; it++) {
            bool done = false;
            static_for<5, 29>([&](auto Tc) {
                constexpr int t = decltype(Tc)::value;
                if (done) return;
                if constexpr (t == 5) {
                    wg_wait<0>();
                    fence_regs(h[0]);
                } else if constexpr (t % 6 == 5) {
                    wg_wait<1>();
                } else if constexpr (t == SG_EPI) {
                    wg_wait<2>();
                    fence_regs(acc2);
                }
                if constexpr (t % 6 == 5) fence_regs(h[((t + 1) / 6) & 1]);
                if constexpr (t == SG_LD) mbar_wait(bars + 8 * (B_STG_FULL + wg), (it + 1) & 1);
                if constexpr (t == SG_OUT) out_ready();
                if constexpr (t == SG_SUM + 1) arrive(B_STG_EMPTY);
                if constexpr (t == SG_EPI) {
                    mbar_wait(bars + 8 * (B_OUT_FREE + wg), it & 1);
                    if (it == NT / 2 - 1) { done = true; return; }
                }
                constexpr bool g1seg = t % 6 >= 1 && t % 6 <= 3;
                if constexpr (t <= 25 || g1seg) {
                    WG_FENCE();
                    if constexpr (t <= 25) {
#pragma unroll
                        for (int j = (t == 5 ? 0 : t - 2); j <= t - 2; j++) gemm2_step(acc2, p[j], w2desc, j);
                    }
                    if constexpr (g1seg) {
                        if constexpr (t == 25) WG_COMMIT();
                        constexpr int c = (t / 6 + 1) % 4;
                        gemm1_step(h[c & 1], a, w1desc, c, (t % 6 - 1) * 2);
                        gemm1_step(h[c & 1], a, w1desc, c, (t % 6 - 1) * 2 + 1);
                    }
                    WG_COMMIT();
                }
                gelu(Tc);
                if constexpr (t >= SG_EPI) {
#pragma unroll
                    for (int i = 3 * (t - SG_EPI); i < 3 * (t - SG_EPI) + 3; i++) store_out(i);
                }
                layernorm(Tc);
                SCHED_FENCE();
            });
            if (done) break;
            wg_wait<0>();
        }
        wg_wait<0>();
        fence_regs(acc2);
#pragma unroll
        for (int i = 0; i < 6; i++) store_out(i);
        out_ready();
        TRS_(4);
    }
}

typedef CUresult (*PFN_encodeTiled)(CUtensorMap*, CUtensorMapDataType, cuuint32_t, void*, const cuuint64_t*,
                                    const cuuint64_t*, const cuuint32_t*, const cuuint32_t*, CUtensorMapInterleave,
                                    CUtensorMapSwizzle, CUtensorMapL2promotion, CUtensorMapFloatOOBfill);

}

extern "C" void kernel_launch(void* const* d_in, const int* in_sizes, int n_in, void* d_out, int out_size) {
    const __nv_bfloat16* x = (const __nv_bfloat16*)d_in[0];
    const __nv_bfloat16* dwl = (const __nv_bfloat16*)d_in[1];
    const __nv_bfloat16* dws = (const __nv_bfloat16*)d_in[2];
    const __nv_bfloat16* w1 = (const __nv_bfloat16*)d_in[3];
    const __nv_bfloat16* w2 = (const __nv_bfloat16*)d_in[4];

    static PFN_encodeTiled encode = nullptr;
    if (!encode) {
        void* fn = nullptr;
        cudaDriverEntryPointQueryResult qres;
        cudaGetDriverEntryPoint("cuTensorMapEncodeTiled", &fn, cudaEnableDefault, &qres);
        encode = (PFN_encodeTiled)fn;
        cudaFuncSetAttribute(fused_block_kernel, cudaFuncAttributeMaxDynamicSharedMemorySize, SMEM_TOTAL);
    }
    CUtensorMap rowmap, tilemap, outmap;
    cuuint64_t gdim[3] = {(cuuint64_t)CH, (cuuint64_t)IMG_W, (cuuint64_t)IMG_H};
    cuuint64_t gstride[2] = {(cuuint64_t)PXB, (cuuint64_t)IMG_W * PXB};
    cuuint32_t estr[3] = {1, 1, 1};
    cuuint32_t box_row[3] = {(cuuint32_t)CH, (cuuint32_t)ROW_PX, (cuuint32_t)TR};
    cuuint32_t box_tile[3] = {(cuuint32_t)CH, (cuuint32_t)BW, (cuuint32_t)TR};
    encode(&rowmap, CU_TENSOR_MAP_DATA_TYPE_BFLOAT16, 3, (void*)x, gdim, gstride, box_row, estr,
           CU_TENSOR_MAP_INTERLEAVE_NONE, CU_TENSOR_MAP_SWIZZLE_NONE, CU_TENSOR_MAP_L2_PROMOTION_L2_256B,
           CU_TENSOR_MAP_FLOAT_OOB_FILL_NONE);
    encode(&tilemap, CU_TENSOR_MAP_DATA_TYPE_BFLOAT16, 3, (void*)x, gdim, gstride, box_tile, estr,
           CU_TENSOR_MAP_INTERLEAVE_NONE, CU_TENSOR_MAP_SWIZZLE_NONE, CU_TENSOR_MAP_L2_PROMOTION_L2_256B,
           CU_TENSOR_MAP_FLOAT_OOB_FILL_NONE);
    encode(&outmap, CU_TENSOR_MAP_DATA_TYPE_BFLOAT16, 3, d_out, gdim, gstride, box_tile, estr,
           CU_TENSOR_MAP_INTERLEAVE_NONE, CU_TENSOR_MAP_SWIZZLE_NONE, CU_TENSOR_MAP_L2_PROMOTION_NONE,
           CU_TENSOR_MAP_FLOAT_OOB_FILL_NONE);
    fused_block_kernel<<<NCTA, NTHREADS, SMEM_TOTAL>>>(rowmap, tilemap, outmap, dwl, dws, w1, w2);
}
```

```cpp
#include <cuda_runtime.h>
#include <cuda_bf16.h>
#include <cuda.h>
#include <stdint.h>
#include <type_traits>

#define TRS_(i)
#define PTR_(k)

namespace {

constexpr int IMG_H = 512, IMG_W = 512, CH = 96, HID = 384;
constexpr int BW = 16;
constexpr int TR = 4;
constexpr int NT = 32;
constexpr int NCTA = (IMG_W / BW) * (IMG_H / (TR * NT));
constexpr int PXB = CH * 2;
constexpr int ROW_PX = BW + 4;
constexpr int ROW_BYTES = ROW_PX * PXB;
constexpr int UNIT_BYTES = TR * ROW_BYTES;
constexpr int STG_PITCH = 208;
constexpr int STG_BYTES = 64 * STG_PITCH;
constexpr int OUT_BYTES = 64 * PXB;
constexpr int NTHREADS = 512;
constexpr int MLP_REGS = 168, TMA_REGS = 24, CONV_REGS = 512 - 2 * MLP_REGS - TMA_REGS;

constexpr int W1_BYTES = CH * HID * 2;
constexpr int W2_BYTES = HID * CH * 2;
constexpr int WPIECE = 24576;
constexpr int SM_W1 = 0;
constexpr int SM_W2 = SM_W1 + W1_BYTES;
constexpr int SM_RING = SM_W2 + W2_BYTES;
constexpr int SM_OUT = SM_RING + 2 * UNIT_BYTES;
constexpr int SM_STG = SM_OUT + 2 * OUT_BYTES;
constexpr int SM_BAR = SM_STG + 2 * STG_BYTES;
constexpr int SMEM_TOTAL = SM_BAR + 256;
static_assert(SMEM_TOTAL <= 232448, "smem");

constexpr int B_RING_FULL = 0;
constexpr int B_RING_EMPTY = 2;
constexpr int B_STG_FULL = 4;
constexpr int B_STG_EMPTY = 6;
constexpr int B_X_FULL = 8;
constexpr int B_OUT_READY = 10;
constexpr int B_OUT_FREE = 12;
constexpr int B_FILTER = 14;
constexpr int B_WEIGHTS = 16;

constexpr int W1_LBO = 8 * HID * 2, W1_SBO = 128;
constexpr int W2_KG = 8 * CH * 2;
constexpr int W2_LBO = 8 * W2_KG, W2_SBO = 128;

constexpr float GELU_S = 0.3292034911525734f;
constexpr uint32_t GELU_CH2 = 0x3FC23FC2u, GELU_CL2 = 0x3B513B51u;
constexpr uint32_t GELU_A2 = 0x40D940D9u;

__device__ __forceinline__ uint32_t smem_u32(const void* p) {
    return (uint32_t)__cvta_generic_to_shared(p);
}
__device__ __forceinline__ uint64_t make_desc(uint32_t addr, uint32_t lbo, uint32_t sbo) {
    return (uint64_t)((addr & 0x3FFFF) >> 4) | ((uint64_t)(lbo >> 4) << 16) | ((uint64_t)(sbo >> 4) << 32);
}
__device__ __forceinline__ void mbar_init(uint32_t bar, uint32_t cnt) {
    asm volatile("mbarrier.init.shared::cta.b64 [%0], %1;" ::"r"(bar), "r"(cnt));
}
__device__ __forceinline__ void mbar_expect_tx(uint32_t bar, uint32_t bytes) {
    asm volatile("mbarrier.arrive.expect_tx.shared::cta.b64 _, [%0], %1;" ::"r"(bar), "r"(bytes) : "memory");
}
__device__ __forceinline__ void mbar_arrive_if(uint32_t bar, bool pred) {
    asm volatile("{\n.reg .pred p;\nsetp.ne.u32 p, %1, 0;\n@p mbarrier.arrive.shared::cta.b64 _, [%0];\n}\n"
                 ::"r"(bar), "r"((uint32_t)pred) : "memory");
}
__device__ __forceinline__ void mbar_wait(uint32_t bar, uint32_t parity) {
    asm volatile(
        "{\n"
        ".reg .pred p;\n"
        "WAIT_LOOP:\n"
        "mbarrier.try_wait.parity.shared::cta.b64 p, [%0], %1, %2;\n"
        "@p bra WAIT_DONE;\n"
        "bra WAIT_LOOP;\n"
        "WAIT_DONE:\n"
        "}\n" ::"r"(bar), "r"(parity), "r"(20000) : "memory");
}
__device__ __forceinline__ void tma_load3d(uint32_t dst, const CUtensorMap* map, int cx, int cy, uint32_t bar) {
    asm volatile(
        "cp.async.bulk.tensor.3d.shared::cluster.global.mbarrier::complete_tx::bytes [%0], [%1, {%2, %3, %4}], [%5];"
        ::"r"(dst), "l"((uint64_t)map), "r"(0), "r"(cx), "r"(cy), "r"(bar) : "memory");
}
__device__ __forceinline__ void bulk_load(uint32_t dst, const void* src, uint32_t bytes, uint32_t bar) {
    asm volatile("cp.async.bulk.shared::cluster.global.mbarrier::complete_tx::bytes [%0], [%1], %2, [%3];"
                 ::"r"(dst), "l"(src), "r"(bytes), "r"(bar) : "memory");
}
__device__ __forceinline__ uint4 lds128(uint32_t addr) {
    uint4 v;
    asm volatile("ld.shared.v4.u32 {%0,%1,%2,%3}, [%4];" : "=r"(v.x), "=r"(v.y), "=r"(v.z), "=r"(v.w) : "r"(addr));
    return v;
}
__device__ __forceinline__ uint32_t lds32(uint32_t addr) {
    uint32_t v;
    asm volatile("ld.shared.u32 %0, [%1];" : "=r"(v) : "r"(addr));
    return v;
}
__device__ __forceinline__ void sts128(uint32_t addr, uint4 v) {
    asm volatile("st.shared.v4.u32 [%0], {%1,%2,%3,%4};" ::"r"(addr), "r"(v.x), "r"(v.y), "r"(v.z), "r"(v.w) : "memory");
}
__device__ __forceinline__ void sts32(uint32_t addr, uint32_t a) {
    asm volatile("st.shared.u32 [%0], %1;" ::"r"(addr), "r"(a) : "memory");
}
__device__ __forceinline__ void ldsm4(uint32_t& a, uint32_t& b, uint32_t& c, uint32_t& d, uint32_t addr) {
    asm volatile("ldmatrix.sync.aligned.m8n8.x4.shared.b16 {%0,%1,%2,%3}, [%4];"
                 : "=r"(a), "=r"(b), "=r"(c), "=r"(d) : "r"(addr));
}
__device__ __forceinline__ void ldsm2(uint32_t& a, uint32_t& b, uint32_t addr) {
    asm volatile("ldmatrix.sync.aligned.m8n8.x2.shared.b16 {%0,%1}, [%2];" : "=r"(a), "=r"(b) : "r"(addr));
}
__device__ __forceinline__ void stsm4(uint32_t addr, uint32_t a, uint32_t b, uint32_t c, uint32_t d) {
    asm volatile("stmatrix.sync.aligned.m8n8.x4.shared.b16 [%0], {%1,%2,%3,%4};"
                 ::"r"(addr), "r"(a), "r"(b), "r"(c), "r"(d) : "memory");
}
__device__ __forceinline__ void stsm2(uint32_t addr, uint32_t a, uint32_t b) {
    asm volatile("stmatrix.sync.aligned.m8n8.x2.shared.b16 [%0], {%1,%2};" ::"r"(addr), "r"(a), "r"(b) : "memory");
}
__device__ __forceinline__ uint32_t hfma2(uint32_t a, uint32_t b, uint32_t c) {
    uint32_t d;
    asm("fma.rn.bf16x2 %0, %1, %2, %3;" : "=r"(d) : "r"(a), "r"(b), "r"(c));
    return d;
}
__device__ __forceinline__ uint32_t hmul2(uint32_t a, uint32_t b) {
    uint32_t d;
    asm("mul.rn.bf16x2 %0, %1, %2;" : "=r"(d) : "r"(a), "r"(b));
    return d;
}
__device__ __forceinline__ uint32_t hadd2(uint32_t a, uint32_t b) {
    uint32_t d;
    asm("add.rn.bf16x2 %0, %1, %2;" : "=r"(d) : "r"(a), "r"(b));
    return d;
}
__device__ __forceinline__ uint32_t hsub2(uint32_t a, uint32_t b) {
    uint32_t d;
    asm("sub.rn.bf16x2 %0, %1, %2;" : "=r"(d) : "r"(a), "r"(b));
    return d;
}
__device__ __forceinline__ uint32_t fold(uint32_t a, uint32_t b) {
    return hadd2(__byte_perm(a, b, 0x5410), __byte_perm(a, b, 0x7632));
}
__device__ __forceinline__ float bf_lo(uint32_t v) { return __uint_as_float(v << 16); }
__device__ __forceinline__ float bf_hi(uint32_t v) { return __uint_as_float(v & 0xffff0000u); }
__device__ __forceinline__ uint32_t pack_bf16(float lo, float hi) {
    uint32_t d;
    asm("cvt.rn.bf16x2.f32 %0, %1, %2;" : "=r"(d) : "f"(hi), "f"(lo));
    return d;
}
__device__ __forceinline__ uint32_t pack_f16(float lo, float hi) {
    uint32_t d;
    asm("cvt.rn.f16x2.f32 %0, %1, %2;" : "=r"(d) : "f"(hi), "f"(lo));
    return d;
}
__device__ __forceinline__ uint32_t bf2h(uint32_t v) { return pack_f16(bf_lo(v), bf_hi(v)); }
__device__ __forceinline__ uint4 bf2h4(uint4 v) { return make_uint4(bf2h(v.x), bf2h(v.y), bf2h(v.z), bf2h(v.w)); }
__device__ __forceinline__ uint32_t mulc(uint32_t v) { return hfma2(v, GELU_CH2, hmul2(v, GELU_CL2)); }
__device__ __forceinline__ uint32_t h2bf(uint32_t h) {
    float lo, hi;
    asm("{\n.reg .b16 l, h;\nmov.b32 {l, h}, %2;\ncvt.f32.f16 %0, l;\ncvt.f32.f16 %1, h;\n}\n" : "=f"(lo), "=f"(hi) : "r"(h));
    return pack_bf16(lo, hi);
}

#define WG_FENCE() asm volatile("wgmma.fence.sync.aligned;" ::: "memory")
#define WG_COMMIT() asm volatile("wgmma.commit_group.sync.aligned;" ::: "memory")
template <int N>
__device__ __forceinline__ void wg_wait() {
    asm volatile("wgmma.wait_group.sync.aligned %0;" ::"n"(N) : "memory");
}
#define SCHED_FENCE() asm volatile("pmevent.mask 0;" ::: "memory")

template <bool ACC>
__device__ __forceinline__ void wgmma_rs(uint32_t (&d)[24], const uint32_t (&a)[4], uint64_t desc) {
    asm volatile(
        "{\n"
        ".reg .pred p;\n"
        "setp.ne.b32 p, %29, 0;\n"
        "wgmma.mma_async.sync.aligned.m64n96k16.f16.f16.f16 {"
        "%0,%1,%2,%3,%4,%5,%6,%7,%8,%9,%10,%11,%12,%13,%14,%15,"
        "%16,%17,%18,%19,%20,%21,%22,%23"
        "}, {%24,%25,%26,%27}, %28, p, 1, 1, 1;\n"
        "}\n"
        : "+r"(d[0]), "+r"(d[1]), "+r"(d[2]), "+r"(d[3]), "+r"(d[4]), "+r"(d[5]), "+r"(d[6]), "+r"(d[7]),
          "+r"(d[8]), "+r"(d[9]), "+r"(d[10]), "+r"(d[11]), "+r"(d[12]), "+r"(d[13]), "+r"(d[14]), "+r"(d[15]),
          "+r"(d[16]), "+r"(d[17]), "+r"(d[18]), "+r"(d[19]), "+r"(d[20]), "+r"(d[21]), "+r"(d[22]), "+r"(d[23])
        : "r"(a[0]), "r"(a[1]), "r"(a[2]), "r"(a[3]), "l"(desc), "n"(ACC ? 1 : 0));
}
__device__ __forceinline__ void gemm1_step(uint32_t (&h)[24], const uint32_t (&a)[6][4], uint64_t w1desc, int c, int ks) {
    const uint64_t d = w1desc + (uint64_t)((c * 12 * W1_SBO + ks * 2 * W1_LBO) >> 4);
    if (ks == 0) wgmma_rs<false>(h, a[0], d);
    else wgmma_rs<true>(h, a[ks], d);
}
__device__ __forceinline__ void gemm2_step(uint32_t (&acc2)[24], const uint32_t (&p)[4], uint64_t w2desc, int j) {
    const uint64_t d = w2desc + (uint64_t)(((16 * (j % 3) + j / 3) * W2_KG) >> 4);
    if (j == 0) wgmma_rs<false>(acc2, p, d);
    else wgmma_rs<true>(acc2, p, d);
}
__device__ __forceinline__ uint32_t gelu_front(uint32_t y) {
    uint32_t t, u;
    asm("fma.rn.f16x2 %0, %1, %1, %2;" : "=r"(t) : "r"(y), "r"(GELU_A2));
    asm("mul.rn.f16x2 %0, %1, %2;" : "=r"(u) : "r"(y), "r"(t));
    return u;
}
__device__ __forceinline__ void gelu_tanh(uint16_t& lo, uint16_t& hi, uint32_t u) {
    asm("{\n.reg .b16 l, h;\nmov.b32 {l, h}, %2;\ntanh.approx.f16 %0, l;\ntanh.approx.f16 %1, h;\n}\n"
        : "=h"(lo), "=h"(hi) : "r"(u));
}
__device__ __forceinline__ uint32_t gelu_back(uint32_t y, uint16_t lo, uint16_t hi) {
    uint32_t g;
    asm("{\n.reg .b32 t;\nmov.b32 t, {%2, %3};\nfma.rn.f16x2 %0, %1, t, %1;\n}\n" : "=r"(g) : "r"(y), "h"(lo), "h"(hi));
    return g;
}

template <int B, int E, typename F>
__device__ __forceinline__ void static_for(F&& f) {
    if constexpr (B < E) {
        f(std::integral_constant<int, B>{});
        static_for<B + 1, E>(f);
    }
}

template <int NP, int R0>
__device__ __forceinline__ void conv_row(uint32_t (&o)[2 * NP], uint32_t (&acc)[4][NP][3], const uint32_t (&w)[5][7],
                                         const uint32_t (&x)[2 * NP + 4]) {
    uint32_t e[NP + 1], f[NP + 1], t[5][NP][3];
#pragma unroll
    for (int i = 0; i <= NP; i++) {
        e[i] = hsub2(x[2 * i], x[2 * i + 1]);
        f[i] = hsub2(x[2 * i + 2], x[2 * i + 1]);
    }
#pragma unroll
    for (int p = 0; p < NP; p++) {
#pragma unroll
        for (int r = R0; r < 5; r++) {
            const uint32_t(&h)[7] = w[4 - r];
            t[r][p][1] = r < 4 ? hfma2(x[2 * p + 1], h[3], acc[r & 3][p][1]) : hmul2(x[2 * p + 1], h[3]);
            t[r][p][0] = r < 4 ? hfma2(x[2 * p + 4], h[2], acc[r & 3][p][0]) : hmul2(x[2 * p + 4], h[2]);
            t[r][p][2] = r < 4 ? hfma2(x[2 * p + 5], h[2], acc[r & 3][p][2]) : hmul2(x[2 * p + 5], h[2]);
        }
#pragma unroll
        for (int r = R0; r < 5; r++) {
            const uint32_t(&h)[7] = w[4 - r];
            t[r][p][1] = hfma2(x[2 * p + 3], h[4], t[r][p][1]);
            t[r][p][0] = hfma2(e[p], h[0], t[r][p][0]);
            t[r][p][2] = hfma2(f[p], h[5], t[r][p][2]);
        }
#pragma unroll
        for (int r = R0; r < 5; r++) {
            const uint32_t(&h)[7] = w[4 - r];
            t[r][p][0] = hfma2(e[p + 1], h[1], t[r][p][0]);
            t[r][p][2] = hfma2(f[p + 1], h[6], t[r][p][2]);
        }
        if (R0 == 0) {
            o[2 * p] = hadd2(t[0][p][0], t[0][p][1]);
            o[2 * p + 1] = hadd2(t[0][p][1], t[0][p][2]);
        }
#pragma unroll
        for (int r = (R0 > 0 ? R0 : 1); r < 5; r++)
#pragma unroll
            for (int m = 0; m < 3; m++) acc[r - 1][p][m] = t[r][p][m];
    }
}

constexpr int SG_LD = 11, SG_S0 = 12, SG_SUM = 14, SG_SH2 = 15, SG_RS = 16, SG_CVT = 18;
constexpr int SG_OUT = 7;
constexpr int SG_EPI = 27;

__global__ void __launch_bounds__(NTHREADS, 1)
fused_block_kernel(const __grid_constant__ CUtensorMap rowmap, const __grid_constant__ CUtensorMap tilemap,
                   const __grid_constant__ CUtensorMap outmap,
                   const __nv_bfloat16* __restrict__ dwl, const __nv_bfloat16* __restrict__ dws,
                   const __nv_bfloat16* __restrict__ w1, const __nv_bfloat16* __restrict__ w2) {
    extern __shared__ __align__(1024) uint8_t smem[];
    const uint32_t sbase = smem_u32(smem);
    const int tid = threadIdx.x;
    const int wid = __shfl_sync(0xffffffffu, tid >> 5, 0);
    const int wg = wid >> 2, warp = wid & 3;
    const int lane = tid & 31;
    const uint32_t bars = sbase + SM_BAR;
    const int x0 = (blockIdx.x >> 2) * BW, y0 = (blockIdx.x & 3) * (TR * NT);

    if (tid == NTHREADS - 128) {
        const char* w1b = reinterpret_cast<const char*>(w1);
        const char* w2b = reinterpret_cast<const char*>(w2);
        asm volatile("cp.async.bulk.prefetch.L2.global [%0], %1;"
                     ::"l"(((blockIdx.x & 1) ? w2b : w1b) + (blockIdx.x >> 1) * (W1_BYTES / (NCTA / 2))), "r"(W1_BYTES / (NCTA / 2))
                     : "memory");
        mbar_init(bars + 8 * B_FILTER, 1);
        mbar_init(bars + 8 * B_RING_FULL, 1);
        mbar_init(bars + 8 * B_RING_FULL + 8, 1);
#pragma unroll
        for (int i = 0; i < 6; i++) mbar_init(bars + 8 * (B_WEIGHTS + i), 1);
        asm volatile("fence.mbarrier_init.release.cluster;" ::: "memory");
        mbar_expect_tx(bars + 8 * B_FILTER, 34 * PXB);
        bulk_load(sbase + SM_OUT, dws, 25 * PXB, bars + 8 * B_FILTER);
        bulk_load(sbase + SM_OUT + 25 * PXB, dwl, 9 * PXB, bars + 8 * B_FILTER);
#pragma unroll
        for (int i = 0; i < 6; i++) {
            if (i < 2) {
                mbar_expect_tx(bars + 8 * (B_RING_FULL + i), UNIT_BYTES);
                tma_load3d(sbase + SM_RING + i * UNIT_BYTES, &rowmap, x0 - 2, y0 - 2 + TR * i, bars + 8 * (B_RING_FULL + i));
            }
            mbar_expect_tx(bars + 8 * (B_WEIGHTS + i), WPIECE);
            bulk_load(sbase + i * WPIECE, (i < 3 ? w1b : w2b) + (i % 3) * WPIECE, WPIECE, bars + 8 * (B_WEIGHTS + i));
        }
    } else if (tid == NTHREADS - 96) {
#pragma unroll
        for (int m = 0; m < 2; m++) {
            mbar_init(bars + 8 * (B_RING_EMPTY + m), 4);
            mbar_init(bars + 8 * (B_STG_FULL + m), 4);
            mbar_init(bars + 8 * (B_STG_EMPTY + m), 4);
                        mbar_init(bars + 8 * (B_X_FULL + m), 1);
            mbar_init(bars + 8 * (B_OUT_READY + m), 4);
            mbar_init(bars + 8 * (B_OUT_FREE + m), 1);
        }
        asm volatile("fence.mbarrier_init.release.cluster;" ::: "memory");
    }
    __syncthreads();

    if (wg == 3) {
        asm volatile("setmaxnreg.dec.sync.aligned.u32 %0;" ::"n"(TMA_REGS));
        const int m = warp >> 1;
        if (lane == 0) {
            if (warp == 0 || warp == 3) {
                const uint32_t fb = bars + 8 * (B_RING_FULL + m);
#pragma unroll 1
                for (int j = m + 2; j <= NT; j += 2) {
                    mbar_wait(bars + 8 * (B_RING_EMPTY + m), ((j >> 1) & 1) ^ 1);
                    mbar_expect_tx(fb, UNIT_BYTES);
                    tma_load3d(sbase + SM_RING + m * UNIT_BYTES, &rowmap, x0 - 2, y0 - 2 + TR * j, fb);
                }
                if (m == 1) {
                    mbar_wait(bars + 8 * (B_RING_EMPTY + m), ((NT >> 1) & 1) ^ 1);
                    mbar_arrive_if(fb, true);
                }
            } else {
                const uint32_t fb = bars + 8 * (B_X_FULL + m), buf = sbase + SM_OUT + m * OUT_BYTES;
                mbar_wait(bars + 8 * (B_OUT_READY + m), 0);
#pragma unroll 1
                for (int i = 0; i < NT / 2; i++) {
                    const int cy = y0 + TR * (2 * i + m);
                    PTR_(0);
                    mbar_expect_tx(fb, OUT_BYTES);
                    tma_load3d(buf, &tilemap, x0, cy, fb);
                    mbar_wait(fb, i & 1);
                    PTR_(1);
                    asm volatile("cp.async.bulk.tensor.3d.global.shared::cta.bulk_group [%0, {%1, %2, %3}], [%4];"
                                 ::"l"((uint64_t)&outmap), "r"(0), "r"(x0), "r"(cy), "r"(buf) : "memory");
                    asm volatile("cp.async.bulk.commit_group;" ::: "memory");
                    asm volatile("cp.async.bulk.wait_group 0;" ::: "memory");
                    PTR_(2);
                    mbar_arrive_if(bars + 8 * (B_OUT_FREE + m), true);
                    mbar_wait(bars + 8 * (B_OUT_READY + m), (i & 1) ^ 1);
                    PTR_(3);
                    asm volatile("cp.reduce.async.bulk.tensor.3d.global.shared::cta.add.bulk_group [%0, {%1, %2, %3}], [%4];"
                                 ::"l"((uint64_t)&outmap), "r"(0), "r"(x0), "r"(cy), "r"(buf) : "memory");
                    asm volatile("cp.async.bulk.commit_group;" ::: "memory");
                    asm volatile("cp.async.bulk.wait_group 0;" ::: "memory");
                    PTR_(4);
                }
            }
        }
    } else if (wg == 2) {
        asm volatile("setmaxnreg.inc.sync.aligned.u32 %0;" ::"n"(CONV_REGS));
        uint32_t wa[5][7], wb[5][7];
        {
            const uint32_t pa = sbase + SM_OUT + 4 * lane, pb = sbase + SM_OUT + 4 * (32 + (lane & 15));
            const bool mir = lane >= 16;
            mbar_wait(bars + 8 * B_FILTER, 0);
#pragma unroll
            for (int r = 0; r < 5; r++) {
                uint32_t u[5], v[5];
#pragma unroll
                for (int c = 0; c < 5; c++) {
                    u[c] = lds32(pa + (5 * r + c) * PXB);
                    v[c] = lds32(pb + (5 * r + c) * PXB);
                    if (r >= 1 && r <= 3 && c >= 1 && c <= 3) {
                        u[c] = hadd2(u[c], lds32(pa + (25 + 3 * (r - 1) + c - 1) * PXB));
                        v[c] = hadd2(v[c], lds32(pb + (25 + 3 * (r - 1) + c - 1) * PXB));
                    }
                }
#pragma unroll
                for (int c = 0; c < 2; c++) {
                    const uint32_t lo = v[c], hi = v[4 - c];
                    v[c] = mir ? hi : lo;
                    v[4 - c] = mir ? lo : hi;
                }
                wa[r][0] = u[0]; wa[r][1] = u[2]; wa[r][2] = u[4]; wa[r][3] = hadd2(u[0], u[1]);
                wa[r][4] = hadd2(u[2], u[3]); wa[r][5] = u[1]; wa[r][6] = u[3];
                wb[r][0] = v[0]; wb[r][1] = v[2]; wb[r][2] = v[4]; wb[r][3] = hadd2(v[0], v[1]);
                wb[r][4] = hadd2(v[2], v[3]); wb[r][5] = v[1]; wb[r][6] = v[3];
            }
        }
        const int mi = lane >> 3, mr = lane & 7, up = mr >> 2;
        const uint32_t ring_a = sbase + SM_RING + (4 * warp + mi) * PXB + mr * 16;
        const uint32_t ring_b0 = sbase + SM_RING + (4 * warp + (up ? 7 - mi : mi)) * PXB + 128 + (mr & 3) * 16;
        const uint32_t ring_b1 = sbase + SM_RING + (4 * warp + (up ? 3 - mi : 4 + mi)) * PXB + 128 + (mr & 3) * 16;
        const uint32_t stg_a = sbase + SM_STG + (4 * warp + mi) * STG_PITCH + mr * 16;
        const uint32_t stg_b = sbase + SM_STG + (4 * warp + (up ? 3 - mi : mi)) * STG_PITCH + 128 + (mr & 3) * 16;
        uint32_t acca[4][2][3], accb[4][1][3], xa[8], xb[6], oa[4], ob[2];
        auto fetch_a = [&](uint32_t off) {
            ldsm4(xa[0], xa[1], xa[2], xa[3], ring_a + off);
            ldsm4(xa[4], xa[5], xa[6], xa[7], ring_a + off + 4 * PXB);
        };
        auto fetch_b = [&](uint32_t off) {
            ldsm4(xb[0], xb[1], xb[2], xb[3], ring_b0 + off);
            ldsm2(xb[4], xb[5], ring_b1 + off);
        };
        const uint32_t arr = bars + 8 * (lane == 0 ? B_RING_EMPTY + 1 : B_STG_FULL);
        TRS_(0);
        mbar_wait(bars + 8 * B_RING_FULL, 0);
        TRS_(1);
        static_for<0, 4>([&](auto Rc) {
            constexpr int R = decltype(Rc)::value;
            fetch_a(R * ROW_BYTES);
            fetch_b(R * ROW_BYTES);
            conv_row<2, 4 - R>(oa, acca, wa, xa);
            conv_row<1, 4 - R>(ob, accb, wb, xb);
        });
        SCHED_FENCE();
        __syncwarp();
        mbar_arrive_if(bars + 8 * B_RING_EMPTY, lane == 0);
        mbar_wait(bars + 8 * (B_RING_FULL + 1), 0);
        fetch_a(UNIT_BYTES);
        fetch_b(UNIT_BYTES);
        TRS_(5);
#pragma unroll 1
        for (int k0 = 0; k0 < NT; k0 += 2) {
#pragma unroll
            for (int kk = 0; kk < 2; kk++) {
                const uint32_t s = kk, ph = ((k0 >> 1) & 1) ^ 1;
                const uint32_t nxt = s * UNIT_BYTES, cur = nxt ^ UNIT_BYTES, dst = s * STG_BYTES;
#pragma unroll
                for (int R = 0; R < 4; R++) {
                    conv_row<2, 0>(oa, acca, wa, xa);
                    if (R == 0) mbar_wait(bars + 8 * B_STG_EMPTY + 8 * s, ph);
                    if (R == 3) mbar_wait(bars + 8 * B_RING_FULL + 8 * s, ph);
                    fetch_a(R < 3 ? cur + (R + 1) * ROW_BYTES : nxt);
                    stsm4(stg_a + dst + R * (BW * STG_PITCH), oa[0], oa[1], oa[2], oa[3]);
                    conv_row<1, 0>(ob, accb, wb, xb);
                    fetch_b(R < 3 ? cur + (R + 1) * ROW_BYTES : nxt);
                    stsm2(stg_b + dst + R * (BW * STG_PITCH), ob[0], ob[1]);
                    if (R == 3) {
                        __syncwarp();
                        mbar_arrive_if(arr ^ (8 * s), lane < 2);
                    }
                    if (R < 3 || kk == 0) SCHED_FENCE();
                }
            }
        }
#pragma unroll
        for (int s = 0; s < 2; s++) {
            mbar_wait(bars + 8 * B_STG_EMPTY + 8 * s, 1);
            mbar_arrive_if(bars + 8 * B_STG_FULL + 8 * s, lane == 0);
        }
        TRS_(4);
    } else {
        asm volatile("setmaxnreg.inc.sync.aligned.u32 %0;" ::"n"(MLP_REGS));
        TRS_(0);
        {
            const int kk = lane & 7, a0 = (kk + (lane >> 3)) & 7;
#pragma unroll 1
            for (int t = wid; t < 24; t += 8) {
                const uint32_t base = sbase + SM_W1 + (t >> 1) * W1_LBO + (t & 1) * 384;
                uint4 v[6];
                mbar_wait(bars + 8 * (B_WEIGHTS + (t >> 3)), 0);
#pragma unroll
                for (int i = 0; i < 6; i++) v[i] = lds128(base + (i >> 1) * 128 + kk * (HID * 2) + (a0 ^ ((i & 1) * 4)) * 16);
                __syncwarp();
#pragma unroll
                for (int i = 0; i < 6; i++)
                    sts128(base + (i >> 1) * 128 + (a0 ^ ((i & 1) * 4)) * (HID * 2) + kk * 16, bf2h4(v[i]));
            }
            TRS_(1);
            const int q2 = lane & 3, k2 = lane >> 2;
#pragma unroll 1
            for (int t = wid; t < 48; t += 8) {
                const uint32_t base = sbase + SM_W2 + t * W2_KG;
                uint4 v[3];
                mbar_wait(bars + 8 * (B_WEIGHTS + 3 + (t >> 4)), 0);
#pragma unroll
                for (int i = 0; i < 3; i++) v[i] = lds128(base + k2 * (CH * 2) + i * 64 + q2 * 16);
                __syncwarp();
#pragma unroll
                for (int i = 0; i < 3; i++) {
                    const uint32_t d = base + i * 512 + k2 * 16 + q2 * 4;
                    const uint4 c = bf2h4(make_uint4(mulc(v[i].x), mulc(v[i].y), mulc(v[i].z), mulc(v[i].w)));
                    sts32(d, c.x);
                    sts32(d + 128, c.y);
                    sts32(d + 256, c.z);
                    sts32(d + 384, c.w);
                }
            }
            asm volatile("fence.proxy.async.shared::cta;" ::: "memory");
            asm volatile("bar.sync 1, 256;" ::: "memory");
            TRS_(2);
        }

        const uint64_t w1desc = make_desc(sbase + SM_W1, W1_LBO, W1_SBO);
        const uint64_t w2desc = make_desc(sbase + SM_W2, W2_LBO, W2_SBO);
        const uint32_t ldm_addr = sbase + SM_STG + wg * STG_BYTES +
                                  (16 * warp + (lane & 7) + ((lane >> 3) & 1) * 8) * STG_PITCH + (lane >> 4) * 16;
        const uint32_t out_addr = sbase + SM_OUT + wg * OUT_BYTES + (16 * warp + (lane >> 2)) * PXB + (lane & 3) * 16;

        uint32_t a[6][4], r[6][4];
        uint32_t h[2][24], acc2[24];
        uint32_t p[24][4], u[2][4];
        uint16_t tl[2][4], tg[2][4];
        uint32_t ps[2], sq[4], rp[2], cp[2], st[2], sx[2];
        auto fence_regs = [&](auto& v) {
#pragma unroll
            for (int i = 0; i < (int)(sizeof(v) / 4); i++) asm volatile("" : "+r"(v[i]) :: "memory");
        };
#pragma unroll
        for (int i = 0; i < 24; i++) acc2[i] = h[0][i] = h[1][i] = 0u;
        fence_regs(acc2);
        fence_regs(h[0]);
        fence_regs(h[1]);

        auto layernorm = [&](auto Tc) {
            constexpr int t = decltype(Tc)::value;
            if constexpr (t == SG_LD || t == SG_LD + 1) {
#pragma unroll
                for (int ks = 3 * (t - SG_LD); ks < 3 * (t - SG_LD) + 3; ks++)
                    ldsm4(r[ks][0], r[ks][1], r[ks][2], r[ks][3], ldm_addr + ks * 32);
            }
            if constexpr (t >= SG_S0 && t <= SG_SUM) {
                constexpr int k0 = 2 * (t - SG_S0);
#pragma unroll
                for (int j = 0; j < 2; j++) {
                    const uint32_t v = hadd2(hadd2(r[k0][j], r[k0][j + 2]), hadd2(r[k0 + 1][j], r[k0 + 1][j + 2]));
                    ps[j] = k0 == 0 ? v : hadd2(ps[j], v);
                }
#pragma unroll
                for (int ks = k0; ks < k0 + 2; ks++)
#pragma unroll
                    for (int j = 0; j < 4; j++)
                        sq[j] = ks == 0 ? hmul2(r[ks][j], r[ks][j]) : hfma2(r[ks][j], r[ks][j], sq[j]);
            }
            if constexpr (t == SG_SUM) {
                st[0] = fold(ps[0], ps[1]);
                st[1] = fold(hadd2(sq[0], sq[2]), hadd2(sq[1], sq[3]));
#pragma unroll
                for (int i = 0; i < 2; i++) sx[i] = __shfl_xor_sync(0xffffffffu, st[i], 1);
            }
            if constexpr (t == SG_SH2) {
#pragma unroll
                for (int i = 0; i < 2; i++) {
                    st[i] = hadd2(st[i], sx[i]);
                    sx[i] = __shfl_xor_sync(0xffffffffu, st[i], 2);
                }
            }
            if constexpr (t == SG_RS) {
                const uint32_t s1 = hadd2(st[0], sx[0]), s2 = hadd2(st[1], sx[1]);
                float nm[2], var[2];
                bool poor = false;
#pragma unroll
                for (int j = 0; j < 2; j++) {
                    nm[j] = (j ? bf_hi(s1) : bf_lo(s1)) * (-1.0f / CH);
                    const float m2 = nm[j] * nm[j];
                    var[j] = fmaf(j ? bf_hi(s2) : bf_lo(s2), 1.0f / CH, -m2);
                    poor |= !(4.0f * m2 <= var[j]);
                }
                if (__any_sync(0xffffffffu, poor)) {
                    uint32_t d1[4], d2[4];
#pragma unroll
                    for (int j = 0; j < 4; j++) {
                        const uint32_t c = pack_bf16(nm[j & 1], nm[j & 1]);
#pragma unroll
                        for (int ks = 0; ks < 6; ks++) {
                            r[ks][j] = hadd2(r[ks][j], c);
                            d1[j] = ks == 0 ? r[ks][j] : hadd2(d1[j], r[ks][j]);
                            d2[j] = ks == 0 ? hmul2(r[ks][j], r[ks][j]) : hfma2(r[ks][j], r[ks][j], d2[j]);
                        }
                    }
                    uint32_t v1 = fold(hadd2(d1[0], d1[2]), hadd2(d1[1], d1[3]));
                    uint32_t v2 = fold(hadd2(d2[0], d2[2]), hadd2(d2[1], d2[3]));
#pragma unroll
                    for (int i = 1; i <= 2; i++) {
                        v1 = hadd2(v1, __shfl_xor_sync(0xffffffffu, v1, i));
                        v2 = hadd2(v2, __shfl_xor_sync(0xffffffffu, v2, i));
                    }
#pragma unroll
                    for (int j = 0; j < 2; j++) {
                        nm[j] = (j ? bf_hi(v1) : bf_lo(v1)) * (-1.0f / CH);
                        var[j] = fmaxf(fmaf(j ? bf_hi(v2) : bf_lo(v2), 1.0f / CH, -nm[j] * nm[j]), 0.f);
                    }
                }
#pragma unroll
                for (int j = 0; j < 2; j++) {
                    constexpr float K = 1.0f / (GELU_S * GELU_S);
                    float rs;
                    asm("rsqrt.approx.ftz.f32 %0, %1;" : "=f"(rs) : "f"(fmaf(var[j], K, K * 1e-5f)));
                    rp[j] = pack_bf16(rs, rs);
                    const float c = nm[j] * bf_lo(rp[j]);
                    cp[j] = pack_bf16(c, c);
                }
            }
            if constexpr (t >= SG_CVT && t < SG_CVT + 3) {
#pragma unroll
                for (int ks = 2 * (t - SG_CVT); ks < 2 * (t - SG_CVT) + 2; ks++)
#pragma unroll
                    for (int j = 0; j < 4; j++) a[ks][j] = bf2h(hfma2(r[ks][j], rp[j & 1], cp[j & 1]));
            }
        };
        auto gelu = [&](auto Tc) {
            constexpr int t = decltype(Tc)::value;
            constexpr int sf = (t + 1) % 24, sb = (t + 23) % 24;
            if constexpr (t >= 0) {
#pragma unroll
                for (int i = 0; i < 4; i++) gelu_tanh(tl[t & 1][i], tg[t & 1][i], u[t & 1][i]);
            }
#pragma unroll
            for (int i = 0; i < 4; i++) u[(t + 1) & 1][i] = gelu_front(h[(sf / 6) & 1][4 * (sf % 6) + i]);
            if constexpr (t >= 1) {
#pragma unroll
                for (int i = 0; i < 4; i++)
                    p[sb][i] = gelu_back(h[(sb / 6) & 1][4 * (sb % 6) + i], tl[(t + 1) & 1][i], tg[(t + 1) & 1][i]);
            }
        };
        auto arrive = [&](int bar) {
            __syncwarp();
            mbar_arrive_if(bars + 8 * (bar + wg), lane == 0);
        };
        auto store_out = [&](int i) {
            const int half = i / 3, j = i % 3;
            sts128(out_addr + half * 8 * PXB + j * 64,
                   make_uint4(h2bf(acc2[8 * j + half]), h2bf(acc2[8 * j + 2 + half]), h2bf(acc2[8 * j + 4 + half]),
                              h2bf(acc2[8 * j + 6 + half])));
        };
        auto out_ready = [&]() {
            asm volatile("fence.proxy.async.shared::cta;" ::: "memory");
            arrive(B_OUT_READY);
        };

        mbar_wait(bars + 8 * (B_STG_FULL + wg), 0);
        TRS_(3);
        static_for<SG_LD, SG_CVT + 3>(layernorm);
        SCHED_FENCE();
        arrive(B_STG_EMPTY);
        WG_FENCE();
#pragma unroll
        for (int ks = 0; ks < 6; ks++) gemm1_step(h[0], a, w1desc, 0, ks);
        WG_COMMIT();
#pragma unroll
        for (int ks = 0; ks < 6; ks++) gemm1_step(h[1], a, w1desc, 1, ks);
        WG_COMMIT();
        wg_wait<1>();
        fence_regs(h[0]);
        static_for<-1, 5>(gelu);
        wg_wait<0>();

#pragma unroll 1
        for (int it = 0;; it++) {
            bool done = false;
            static_for<5, 29>([&](auto Tc) {
                constexpr int t = decltype(Tc)::value;
                if (done) return;
                if constexpr (t == 5) {
                    wg_wait<0>();
                    fence_regs(h[0]);
                } else if constexpr (t % 6 == 5) {
                    wg_wait<1>();
                } else if constexpr (t == SG_EPI) {
                    wg_wait<2>();
                    fence_regs(acc2);
                }
                if constexpr (t % 6 == 5) fence_regs(h[((t + 1) / 6) & 1]);
                if constexpr (t == SG_LD) mbar_wait(bars + 8 * (B_STG_FULL + wg), (it + 1) & 1);
                if constexpr (t == SG_OUT) out_ready();
                if constexpr (t == SG_SUM + 1) arrive(B_STG_EMPTY);
                if constexpr (t == SG_EPI) {
                    mbar_wait(bars + 8 * (B_OUT_FREE + wg), it & 1);
                    if (it == NT / 2 - 1) { done = true; return; }
                }
                constexpr bool g1seg = t % 6 >= 1 && t % 6 <= 3;
                if constexpr (t <= 25 || g1seg) {
                    WG_FENCE();
                    if constexpr (t <= 25) {
#pragma unroll
                        for (int j = (t == 5 ? 0 : t - 2); j <= t - 2; j++) gemm2_step(acc2, p[j], w2desc, j);
                    }
                    if constexpr (g1seg) {
                        if constexpr (t == 25) WG_COMMIT();
                        constexpr int c = (t / 6 + 1) % 4;
                        gemm1_step(h[c & 1], a, w1desc, c, (t % 6 - 1) * 2);
                        gemm1_step(h[c & 1], a, w1desc, c, (t % 6 - 1) * 2 + 1);
                    }
                    WG_COMMIT();
                }
                gelu(Tc);
                if constexpr (t >= SG_EPI) {
#pragma unroll
                    for (int i = 3 * (t - SG_EPI); i < 3 * (t - SG_EPI) + 3; i++) store_out(i);
                }
                layernorm(Tc);
                SCHED_FENCE();
            });
            if (done) break;
            wg_wait<0>();
        }
        wg_wait<0>();
        fence_regs(acc2);
#pragma unroll
        for (int i = 0; i < 6; i++) store_out(i);
        out_ready();
        TRS_(4);
    }
}

typedef CUresult (*PFN_encodeTiled)(CUtensorMap*, CUtensorMapDataType, cuuint32_t, void*, const cuuint64_t*,
                                    const cuuint64_t*, const cuuint32_t*, const cuuint32_t*, CUtensorMapInterleave,
                                    CUtensorMapSwizzle, CUtensorMapL2promotion, CUtensorMapFloatOOBfill);

}

extern "C" void kernel_launch(void* const* d_in, const int* in_sizes, int n_in, void* d_out, int out_size) {
    const __nv_bfloat16* x = (const __nv_bfloat16*)d_in[0];
    const __nv_bfloat16* dwl = (const __nv_bfloat16*)d_in[1];
    const __nv_bfloat16* dws = (const __nv_bfloat16*)d_in[2];
    const __nv_bfloat16* w1 = (const __nv_bfloat16*)d_in[3];
    const __nv_bfloat16* w2 = (const __nv_bfloat16*)d_in[4];

    static PFN_encodeTiled encode = nullptr;
    if (!encode) {
        void* fn = nullptr;
        cudaDriverEntryPointQueryResult qres;
        cudaGetDriverEntryPoint("cuTensorMapEncodeTiled", &fn, cudaEnableDefault, &qres);
        encode = (PFN_encodeTiled)fn;
        cudaFuncSetAttribute(fused_block_kernel, cudaFuncAttributeMaxDynamicSharedMemorySize, SMEM_TOTAL);
    }
    CUtensorMap rowmap, tilemap, outmap;
    cuuint64_t gdim[3] = {(cuuint64_t)CH, (cuuint64_t)IMG_W, (cuuint64_t)IMG_H};
    cuuint64_t gstride[2] = {(cuuint64_t)PXB, (cuuint64_t)IMG_W * PXB};
    cuuint32_t estr[3] = {1, 1, 1};
    cuuint32_t box_row[3] = {(cuuint32_t)CH, (cuuint32_t)ROW_PX, (cuuint32_t)TR};
    cuuint32_t box_tile[3] = {(cuuint32_t)CH, (cuuint32_t)BW, (cuuint32_t)TR};
    encode(&rowmap, CU_TENSOR_MAP_DATA_TYPE_BFLOAT16, 3, (void*)x, gdim, gstride, box_row, estr,
           CU_TENSOR_MAP_INTERLEAVE_NONE, CU_TENSOR_MAP_SWIZZLE_NONE, CU_TENSOR_MAP_L2_PROMOTION_L2_256B,
           CU_TENSOR_MAP_FLOAT_OOB_FILL_NONE);
    encode(&tilemap, CU_TENSOR_MAP_DATA_TYPE_BFLOAT16, 3, (void*)x, gdim, gstride, box_tile, estr,
           CU_TENSOR_MAP_INTERLEAVE_NONE, CU_TENSOR_MAP_SWIZZLE_NONE, CU_TENSOR_MAP_L2_PROMOTION_L2_256B,
           CU_TENSOR_MAP_FLOAT_OOB_FILL_NONE);
    encode(&outmap, CU_TENSOR_MAP_DATA_TYPE_BFLOAT16, 3, d_out, gdim, gstride, box_tile, estr,
           CU_TENSOR_MAP_INTERLEAVE_NONE, CU_TENSOR_MAP_SWIZZLE_NONE, CU_TENSOR_MAP_L2_PROMOTION_NONE,
           CU_TENSOR_MAP_FLOAT_OOB_FILL_NONE);
    fused_block_kernel<<<NCTA, NTHREADS, SMEM_TOTAL>>>(rowmap, tilemap, outmap, dwl, dws, w1, w2);
}
```

```cpp
#include <cuda_runtime.h>
#include <cuda_bf16.h>
#include <cuda.h>
#include <stdint.h>
#include <type_traits>

#define TRS_(i)

namespace {

constexpr int IMG_H = 512, IMG_W = 512, CH = 96, HID = 384;
constexpr int BW = 16;
constexpr int TR = 4;
constexpr int NT = 32;
constexpr int NCTA = (IMG_W / BW) * (IMG_H / (TR * NT));
constexpr int PXB = CH * 2;
constexpr int ROW_PX = BW + 4;
constexpr int ROW_BYTES = ROW_PX * PXB;
constexpr int UNIT_BYTES = 2 * ROW_BYTES;
constexpr int NU = 2 * NT + 2;
constexpr int STG_PITCH = 208;
constexpr int STG_BYTES = 64 * STG_PITCH;
constexpr int OUT_BYTES = 64 * PXB;
constexpr int NTHREADS = 512;
constexpr int MLP_REGS = 168, TMA_REGS = 24, CONV_REGS = 512 - 2 * MLP_REGS - TMA_REGS;

constexpr int W1_BYTES = CH * HID * 2;
constexpr int W2_BYTES = HID * CH * 2;
constexpr int WPIECE = 24576;
constexpr int SM_W1 = 0;
constexpr int SM_W2 = SM_W1 + W1_BYTES;
constexpr int SM_RING = SM_W2 + W2_BYTES;
constexpr int SM_OUT = SM_RING + 4 * UNIT_BYTES;
constexpr int SM_STG = SM_OUT + 2 * OUT_BYTES;
constexpr int SM_BAR = SM_STG + 2 * STG_BYTES;
constexpr int SMEM_TOTAL = SM_BAR + 256;
static_assert(SMEM_TOTAL <= 232448, "smem");

constexpr int B_RING_FULL = 0;
constexpr int B_RING_EMPTY = 4;
constexpr int B_STG_FULL = 8;
constexpr int B_STG_EMPTY = 12;
constexpr int B_OUT_READY = 14;
constexpr int B_OUT_FREE = 16;
constexpr int B_COPIED = 18;
constexpr int B_FILTER = 19;
constexpr int B_WEIGHTS = 20;

constexpr int W1_LBO = 8 * HID * 2, W1_SBO = 128;
constexpr int W2_KG = 8 * CH * 2;
constexpr int W2_LBO = 8 * W2_KG, W2_SBO = 128;

constexpr float GELU_S = 0.3292034911525734f;
constexpr uint32_t GELU_CH2 = 0x3FC23FC2u, GELU_CL2 = 0x3B513B51u;
constexpr uint32_t GELU_A2 = 0x40D940D9u;

__device__ __forceinline__ uint32_t smem_u32(const void* p) {
    return (uint32_t)__cvta_generic_to_shared(p);
}
__device__ __forceinline__ uint64_t make_desc(uint32_t addr, uint32_t lbo, uint32_t sbo) {
    return (uint64_t)((addr & 0x3FFFF) >> 4) | ((uint64_t)(lbo >> 4) << 16) | ((uint64_t)(sbo >> 4) << 32);
}
__device__ __forceinline__ void mbar_init(uint32_t bar, uint32_t cnt) {
    asm volatile("mbarrier.init.shared::cta.b64 [%0], %1;" ::"r"(bar), "r"(cnt));
}
__device__ __forceinline__ void mbar_expect_tx(uint32_t bar, uint32_t bytes) {
    asm volatile("mbarrier.arrive.expect_tx.shared::cta.b64 _, [%0], %1;" ::"r"(bar), "r"(bytes) : "memory");
}
__device__ __forceinline__ void mbar_arrive_if(uint32_t bar, bool pred) {
    asm volatile("{\n.reg .pred p;\nsetp.ne.u32 p, %1, 0;\n@p mbarrier.arrive.shared::cta.b64 _, [%0];\n}\n"
                 ::"r"(bar), "r"((uint32_t)pred) : "memory");
}
__device__ __forceinline__ void mbar_wait(uint32_t bar, uint32_t parity) {
    asm volatile(
        "{\n"
        ".reg .pred p;\n"
        "WAIT_LOOP:\n"
        "mbarrier.try_wait.parity.shared::cta.b64 p, [%0], %1, %2;\n"
        "@p bra WAIT_DONE;\n"
        "bra WAIT_LOOP;\n"
        "WAIT_DONE:\n"
        "}\n" ::"r"(bar), "r"(parity), "r"(20000) : "memory");
}
__device__ __forceinline__ void tma_load3d(uint32_t dst, const CUtensorMap* map, int cx, int cy, uint32_t bar) {
    asm volatile(
        "cp.async.bulk.tensor.3d.shared::cluster.global.mbarrier::complete_tx::bytes [%0], [%1, {%2, %3, %4}], [%5];"
        ::"r"(dst), "l"((uint64_t)map), "r"(0), "r"(cx), "r"(cy), "r"(bar) : "memory");
}
__device__ __forceinline__ void bulk_load(uint32_t dst, const void* src, uint32_t bytes, uint32_t bar) {
    asm volatile("cp.async.bulk.shared::cluster.global.mbarrier::complete_tx::bytes [%0], [%1], %2, [%3];"
                 ::"r"(dst), "l"(src), "r"(bytes), "r"(bar) : "memory");
}
__device__ __forceinline__ uint4 lds128(uint32_t addr) {
    uint4 v;
    asm volatile("ld.shared.v4.u32 {%0,%1,%2,%3}, [%4];" : "=r"(v.x), "=r"(v.y), "=r"(v.z), "=r"(v.w) : "r"(addr));
    return v;
}
__device__ __forceinline__ uint32_t lds32(uint32_t addr) {
    uint32_t v;
    asm volatile("ld.shared.u32 %0, [%1];" : "=r"(v) : "r"(addr));
    return v;
}
__device__ __forceinline__ void sts128(uint32_t addr, uint4 v) {
    asm volatile("st.shared.v4.u32 [%0], {%1,%2,%3,%4};" ::"r"(addr), "r"(v.x), "r"(v.y), "r"(v.z), "r"(v.w) : "memory");
}
__device__ __forceinline__ void sts32(uint32_t addr, uint32_t a) {
    asm volatile("st.shared.u32 [%0], %1;" ::"r"(addr), "r"(a) : "memory");
}
__device__ __forceinline__ void ldsm4(uint32_t& a, uint32_t& b, uint32_t& c, uint32_t& d, uint32_t addr) {
    asm volatile("ldmatrix.sync.aligned.m8n8.x4.shared.b16 {%0,%1,%2,%3}, [%4];"
                 : "=r"(a), "=r"(b), "=r"(c), "=r"(d) : "r"(addr));
}
__device__ __forceinline__ void ldsm2(uint32_t& a, uint32_t& b, uint32_t addr) {
    asm volatile("ldmatrix.sync.aligned.m8n8.x2.shared.b16 {%0,%1}, [%2];" : "=r"(a), "=r"(b) : "r"(addr));
}
__device__ __forceinline__ void stsm4(uint32_t addr, uint32_t a, uint32_t b, uint32_t c, uint32_t d) {
    asm volatile("stmatrix.sync.aligned.m8n8.x4.shared.b16 [%0], {%1,%2,%3,%4};"
                 ::"r"(addr), "r"(a), "r"(b), "r"(c), "r"(d) : "memory");
}
__device__ __forceinline__ void stsm2(uint32_t addr, uint32_t a, uint32_t b) {
    asm volatile("stmatrix.sync.aligned.m8n8.x2.shared.b16 [%0], {%1,%2};" ::"r"(addr), "r"(a), "r"(b) : "memory");
}
__device__ __forceinline__ uint32_t hfma2(uint32_t a, uint32_t b, uint32_t c) {
    uint32_t d;
    asm("fma.rn.bf16x2 %0, %1, %2, %3;" : "=r"(d) : "r"(a), "r"(b), "r"(c));
    return d;
}
__device__ __forceinline__ uint32_t hmul2(uint32_t a, uint32_t b) {
    uint32_t d;
    asm("mul.rn.bf16x2 %0, %1, %2;" : "=r"(d) : "r"(a), "r"(b));
    return d;
}
__device__ __forceinline__ uint32_t hadd2(uint32_t a, uint32_t b) {
    uint32_t d;
    asm("add.rn.bf16x2 %0, %1, %2;" : "=r"(d) : "r"(a), "r"(b));
    return d;
}
__device__ __forceinline__ uint32_t hsub2(uint32_t a, uint32_t b) {
    uint32_t d;
    asm("sub.rn.bf16x2 %0, %1, %2;" : "=r"(d) : "r"(a), "r"(b));
    return d;
}
__device__ __forceinline__ uint32_t fold(uint32_t a, uint32_t b) {
    return hadd2(__byte_perm(a, b, 0x5410), __byte_perm(a, b, 0x7632));
}
__device__ __forceinline__ float bf_lo(uint32_t v) { return __uint_as_float(v << 16); }
__device__ __forceinline__ float bf_hi(uint32_t v) { return __uint_as_float(v & 0xffff0000u); }
__device__ __forceinline__ uint32_t pack_bf16(float lo, float hi) {
    uint32_t d;
    asm("cvt.rn.bf16x2.f32 %0, %1, %2;" : "=r"(d) : "f"(hi), "f"(lo));
    return d;
}
__device__ __forceinline__ uint32_t pack_f16(float lo, float hi) {
    uint32_t d;
    asm("cvt.rn.f16x2.f32 %0, %1, %2;" : "=r"(d) : "f"(hi), "f"(lo));
    return d;
}
__device__ __forceinline__ uint32_t bf2h(uint32_t v) { return pack_f16(bf_lo(v), bf_hi(v)); }
__device__ __forceinline__ uint4 bf2h4(uint4 v) { return make_uint4(bf2h(v.x), bf2h(v.y), bf2h(v.z), bf2h(v.w)); }
__device__ __forceinline__ uint32_t mulc(uint32_t v) { return hfma2(v, GELU_CH2, hmul2(v, GELU_CL2)); }
__device__ __forceinline__ uint32_t h2bf(uint32_t h) {
    float lo, hi;
    asm("{\n.reg .b16 l, h;\nmov.b32 {l, h}, %2;\ncvt.f32.f16 %0, l;\ncvt.f32.f16 %1, h;\n}\n" : "=f"(lo), "=f"(hi) : "r"(h));
    return pack_bf16(lo, hi);
}

#define WG_FENCE() asm volatile("wgmma.fence.sync.aligned;" ::: "memory")
#define WG_COMMIT() asm volatile("wgmma.commit_group.sync.aligned;" ::: "memory")
template <int N>
__device__ __forceinline__ void wg_wait() {
    asm volatile("wgmma.wait_group.sync.aligned %0;" ::"n"(N) : "memory");
}
#define SCHED_FENCE() asm volatile("pmevent.mask 0;" ::: "memory")

template <bool ACC>
__device__ __forceinline__ void wgmma_rs(uint32_t (&d)[24], const uint32_t (&a)[4], uint64_t desc) {
    asm volatile(
        "{\n"
        ".reg .pred p;\n"
        "setp.ne.b32 p, %29, 0;\n"
        "wgmma.mma_async.sync.aligned.m64n96k16.f16.f16.f16 {"
        "%0,%1,%2,%3,%4,%5,%6,%7,%8,%9,%10,%11,%12,%13,%14,%15,"
        "%16,%17,%18,%19,%20,%21,%22,%23"
        "}, {%24,%25,%26,%27}, %28, p, 1, 1, 1;\n"
        "}\n"
        : "+r"(d[0]), "+r"(d[1]), "+r"(d[2]), "+r"(d[3]), "+r"(d[4]), "+r"(d[5]), "+r"(d[6]), "+r"(d[7]),
          "+r"(d[8]), "+r"(d[9]), "+r"(d[10]), "+r"(d[11]), "+r"(d[12]), "+r"(d[13]), "+r"(d[14]), "+r"(d[15]),
          "+r"(d[16]), "+r"(d[17]), "+r"(d[18]), "+r"(d[19]), "+r"(d[20]), "+r"(d[21]), "+r"(d[22]), "+r"(d[23])
        : "r"(a[0]), "r"(a[1]), "r"(a[2]), "r"(a[3]), "l"(desc), "n"(ACC ? 1 : 0));
}
__device__ __forceinline__ void gemm1_step(uint32_t (&h)[24], const uint32_t (&a)[6][4], uint64_t w1desc, int c, int ks) {
    const uint64_t d = w1desc + (uint64_t)((c * 12 * W1_SBO + ks * 2 * W1_LBO) >> 4);
    if (ks == 0) wgmma_rs<false>(h, a[0], d);
    else wgmma_rs<true>(h, a[ks], d);
}
__device__ __forceinline__ void gemm2_step(uint32_t (&acc2)[24], const uint32_t (&p)[4], uint64_t w2desc, int j) {
    const uint64_t d = w2desc + (uint64_t)(((16 * (j % 3) + j / 3) * W2_KG) >> 4);
    if (j == 0) wgmma_rs<false>(acc2, p, d);
    else wgmma_rs<true>(acc2, p, d);
}
__device__ __forceinline__ uint32_t gelu_front(uint32_t y) {
    uint32_t t, u;
    asm("fma.rn.f16x2 %0, %1, %1, %2;" : "=r"(t) : "r"(y), "r"(GELU_A2));
    asm("mul.rn.f16x2 %0, %1, %2;" : "=r"(u) : "r"(y), "r"(t));
    return u;
}
__device__ __forceinline__ void gelu_tanh(uint16_t& lo, uint16_t& hi, uint32_t u) {
    asm("{\n.reg .b16 l, h;\nmov.b32 {l, h}, %2;\ntanh.approx.f16 %0, l;\ntanh.approx.f16 %1, h;\n}\n"
        : "=h"(lo), "=h"(hi) : "r"(u));
}
__device__ __forceinline__ uint32_t gelu_back(uint32_t y, uint16_t lo, uint16_t hi) {
    uint32_t g;
    asm("{\n.reg .b32 t;\nmov.b32 t, {%2, %3};\nfma.rn.f16x2 %0, %1, t, %1;\n}\n" : "=r"(g) : "r"(y), "h"(lo), "h"(hi));
    return g;
}

template <int B, int E, typename F>
__device__ __forceinline__ void static_for(F&& f) {
    if constexpr (B < E) {
        f(std::integral_constant<int, B>{});
        static_for<B + 1, E>(f);
    }
}

template <int NP, int R0>
__device__ __forceinline__ void conv_row(uint32_t (&o)[2 * NP], uint32_t (&acc)[4][NP][3], const uint32_t (&w)[5][7],
                                         const uint32_t (&x)[2 * NP + 4]) {
    uint32_t e[NP + 1], f[NP + 1], t[5][NP][3];
#pragma unroll
    for (int i = 0; i <= NP; i++) {
        e[i] = hsub2(x[2 * i], x[2 * i + 1]);
        f[i] = hsub2(x[2 * i + 2], x[2 * i + 1]);
    }
#pragma unroll
    for (int p = 0; p < NP; p++) {
#pragma unroll
        for (int r = R0; r < 5; r++) {
            const uint32_t(&h)[7] = w[4 - r];
            t[r][p][1] = r < 4 ? hfma2(x[2 * p + 1], h[3], acc[r & 3][p][1]) : hmul2(x[2 * p + 1], h[3]);
            t[r][p][0] = r < 4 ? hfma2(x[2 * p + 4], h[2], acc[r & 3][p][0]) : hmul2(x[2 * p + 4], h[2]);
            t[r][p][2] = r < 4 ? hfma2(x[2 * p + 5], h[2], acc[r & 3][p][2]) : hmul2(x[2 * p + 5], h[2]);
        }
#pragma unroll
        for (int r = R0; r < 5; r++) {
            const uint32_t(&h)[7] = w[4 - r];
            t[r][p][1] = hfma2(x[2 * p + 3], h[4], t[r][p][1]);
            t[r][p][0] = hfma2(e[p], h[0], t[r][p][0]);
            t[r][p][2] = hfma2(f[p], h[5], t[r][p][2]);
        }
#pragma unroll
        for (int r = R0; r < 5; r++) {
            const uint32_t(&h)[7] = w[4 - r];
            t[r][p][0] = hfma2(e[p + 1], h[1], t[r][p][0]);
            t[r][p][2] = hfma2(f[p + 1], h[6], t[r][p][2]);
        }
        if (R0 == 0) {
            o[2 * p] = hadd2(t[0][p][0], t[0][p][1]);
            o[2 * p + 1] = hadd2(t[0][p][1], t[0][p][2]);
        }
#pragma unroll
        for (int r = (R0 > 0 ? R0 : 1); r < 5; r++)
#pragma unroll
            for (int m = 0; m < 3; m++) acc[r - 1][p][m] = t[r][p][m];
    }
}

constexpr int SG_LD = 11, SG_S0 = 12, SG_SUM = 14, SG_SH2 = 15, SG_RS = 16, SG_CVT = 18;
constexpr int SG_OUT = 7;
constexpr int SG_EPI = 27;

__global__ void __launch_bounds__(NTHREADS, 1)
fused_block_kernel(const __grid_constant__ CUtensorMap rowmap, const __grid_constant__ CUtensorMap copymap,
                   const __grid_constant__ CUtensorMap outmap,
                   const __nv_bfloat16* __restrict__ dwl, const __nv_bfloat16* __restrict__ dws,
                   const __nv_bfloat16* __restrict__ w1, const __nv_bfloat16* __restrict__ w2) {
    extern __shared__ __align__(1024) uint8_t smem[];
    const uint32_t sbase = smem_u32(smem);
    const int tid = threadIdx.x;
    const int wid = __shfl_sync(0xffffffffu, tid >> 5, 0);
    const int wg = wid >> 2, warp = wid & 3;
    const int lane = tid & 31;
    const uint32_t bars = sbase + SM_BAR;
    const int x0 = (blockIdx.x >> 2) * BW, y0 = (blockIdx.x & 3) * (TR * NT);

    if (tid == NTHREADS - 128) {
        const char* w1b = reinterpret_cast<const char*>(w1);
        const char* w2b = reinterpret_cast<const char*>(w2);
        asm volatile("cp.async.bulk.prefetch.L2.global [%0], %1;"
                     ::"l"(((blockIdx.x & 1) ? w2b : w1b) + (blockIdx.x >> 1) * (W1_BYTES / (NCTA / 2))), "r"(W1_BYTES / (NCTA / 2))
                     : "memory");
        mbar_init(bars + 8 * B_FILTER, 1);
#pragma unroll
        for (int i = 0; i < 4; i++) mbar_init(bars + 8 * (B_RING_FULL + i), 1);
#pragma unroll
        for (int i = 0; i < 6; i++) mbar_init(bars + 8 * (B_WEIGHTS + i), 1);
        asm volatile("fence.mbarrier_init.release.cluster;" ::: "memory");
        mbar_expect_tx(bars + 8 * B_FILTER, 34 * PXB);
        bulk_load(sbase + SM_OUT, dws, 25 * PXB, bars + 8 * B_FILTER);
        bulk_load(sbase + SM_OUT + 25 * PXB, dwl, 9 * PXB, bars + 8 * B_FILTER);
#pragma unroll
        for (int i = 0; i < 6; i++) {
            if (i < 2) {
#pragma unroll
                for (int u = 2 * i; u < 2 * i + 2; u++) {
                    mbar_expect_tx(bars + 8 * (B_RING_FULL + u), UNIT_BYTES);
                    tma_load3d(sbase + SM_RING + u * UNIT_BYTES, &rowmap, x0 - 2, y0 - 2 + 2 * u, bars + 8 * (B_RING_FULL + u));
                }
            }
            mbar_expect_tx(bars + 8 * (B_WEIGHTS + i), WPIECE);
            bulk_load(sbase + i * WPIECE, (i < 3 ? w1b : w2b) + (i % 3) * WPIECE, WPIECE, bars + 8 * (B_WEIGHTS + i));
        }
    } else if (tid == NTHREADS - 96) {
#pragma unroll
        for (int m = 0; m < 2; m++) {
            mbar_init(bars + 8 * (B_RING_EMPTY + 2 * m), 4);
            mbar_init(bars + 8 * (B_RING_EMPTY + 2 * m + 1), 4);
            mbar_init(bars + 8 * (B_STG_FULL + 2 * m), 4);
            mbar_init(bars + 8 * (B_STG_EMPTY + m), 4);
            mbar_init(bars + 8 * (B_OUT_READY + m), 4);
            mbar_init(bars + 8 * (B_OUT_FREE + m), 1);
        }
        mbar_init(bars + 8 * B_COPIED, 2);
        asm volatile("fence.mbarrier_init.release.cluster;" ::: "memory");
    }
    __syncthreads();

    if (wg == 3) {
        asm volatile("setmaxnreg.dec.sync.aligned.u32 %0;" ::"n"(TMA_REGS));
        const int m = warp >> 1;
        if (lane == 0) {
            if (warp == 0 || warp == 3) {
#pragma unroll 1
                for (int u = 2 * m; u < NU; u += (u & 1) ? 3 : 1) {
                    const uint32_t fb = bars + 8 * (B_RING_FULL + (u & 3)), buf = sbase + SM_RING + (u & 3) * UNIT_BYTES;
                    mbar_wait(bars + 8 * (B_RING_EMPTY + (u & 3)), (u >> 2) & 1);
                    if (u != 0 && u != NU - 1) {
                        asm volatile("cp.async.bulk.tensor.4d.global.shared::cta.bulk_group [%0, {%1, %2, %3, %4}], [%5];"
                                     ::"l"((uint64_t)&copymap), "r"(0), "r"(0), "r"(blockIdx.x >> 2), "r"(y0 - 2 + 2 * u),
                                     "r"(buf + 2 * PXB) : "memory");
                        asm volatile("cp.async.bulk.commit_group;" ::: "memory");
                        asm volatile("cp.async.bulk.wait_group 0;" ::: "memory");
                    }
                    if (u + 4 < NU) {
                        mbar_expect_tx(fb, UNIT_BYTES);
                        tma_load3d(buf, &rowmap, x0 - 2, y0 + 6 + 2 * u, fb);
                    } else {
                        mbar_arrive_if(fb, true);
                    }
                }
                mbar_arrive_if(bars + 8 * B_COPIED, true);
            } else {
                const uint32_t buf = sbase + SM_OUT + m * OUT_BYTES;
#pragma unroll 1
                for (int i = 0; i < NT / 2; i++) {
                    if (i == NT / 2 - 1) mbar_wait(bars + 8 * B_COPIED, 0);
                    mbar_wait(bars + 8 * (B_OUT_READY + m), i & 1);
                    asm volatile("cp.reduce.async.bulk.tensor.3d.global.shared::cta.add.bulk_group [%0, {%1, %2, %3}], [%4];"
                                 ::"l"((uint64_t)&outmap), "r"(0), "r"(x0), "r"(y0 + TR * (2 * i + m)), "r"(buf) : "memory");
                    asm volatile("cp.async.bulk.commit_group;" ::: "memory");
                    asm volatile("cp.async.bulk.wait_group 0;" ::: "memory");
                    mbar_arrive_if(bars + 8 * (B_OUT_FREE + m), true);
                }
            }
        }
    } else if (wg == 2) {
        asm volatile("setmaxnreg.inc.sync.aligned.u32 %0;" ::"n"(CONV_REGS));
        uint32_t wa[5][7], wb[5][7];
        {
            const uint32_t pa = sbase + SM_OUT + 4 * lane, pb = sbase + SM_OUT + 4 * (32 + (lane & 15));
            const bool mir = lane >= 16;
            mbar_wait(bars + 8 * B_FILTER, 0);
#pragma unroll
            for (int r = 0; r < 5; r++) {
                uint32_t u[5], v[5];
#pragma unroll
                for (int c = 0; c < 5; c++) {
                    u[c] = lds32(pa + (5 * r + c) * PXB);
                    v[c] = lds32(pb + (5 * r + c) * PXB);
                    if (r >= 1 && r <= 3 && c >= 1 && c <= 3) {
                        u[c] = hadd2(u[c], lds32(pa + (25 + 3 * (r - 1) + c - 1) * PXB));
                        v[c] = hadd2(v[c], lds32(pb + (25 + 3 * (r - 1) + c - 1) * PXB));
                    }
                }
#pragma unroll
                for (int c = 0; c < 2; c++) {
                    const uint32_t lo = v[c], hi = v[4 - c];
                    v[c] = mir ? hi : lo;
                    v[4 - c] = mir ? lo : hi;
                }
                wa[r][0] = u[0]; wa[r][1] = u[2]; wa[r][2] = u[4]; wa[r][3] = hadd2(u[0], u[1]);
                wa[r][4] = hadd2(u[2], u[3]); wa[r][5] = u[1]; wa[r][6] = u[3];
                wb[r][0] = v[0]; wb[r][1] = v[2]; wb[r][2] = v[4]; wb[r][3] = hadd2(v[0], v[1]);
                wb[r][4] = hadd2(v[2], v[3]); wb[r][5] = v[1]; wb[r][6] = v[3];
            }
        }
        const int mi = lane >> 3, mr = lane & 7, up = mr >> 2;
        const uint32_t ring_a = sbase + SM_RING + (4 * warp + mi) * PXB + mr * 16;
        const uint32_t ring_b0 = sbase + SM_RING + (4 * warp + (up ? 7 - mi : mi)) * PXB + 128 + (mr & 3) * 16;
        const uint32_t ring_b1 = sbase + SM_RING + (4 * warp + (up ? 3 - mi : 4 + mi)) * PXB + 128 + (mr & 3) * 16;
        const uint32_t stg_a = sbase + SM_STG + (4 * warp + mi) * STG_PITCH + mr * 16;
        const uint32_t stg_b = sbase + SM_STG + (4 * warp + (up ? 3 - mi : mi)) * STG_PITCH + 128 + (mr & 3) * 16;
        uint32_t acca[4][2][3], accb[4][1][3], xa[8], xb[6], oa[4], ob[2];
        auto fetch_a = [&](uint32_t off) {
            ldsm4(xa[0], xa[1], xa[2], xa[3], ring_a + off);
            ldsm4(xa[4], xa[5], xa[6], xa[7], ring_a + off + 4 * PXB);
        };
        auto fetch_b = [&](uint32_t off) {
            ldsm4(xb[0], xb[1], xb[2], xb[3], ring_b0 + off);
            ldsm2(xb[4], xb[5], ring_b1 + off);
        };
        const uint32_t arr = bars + 8 * (lane == 0 ? B_RING_EMPTY + 3 : B_STG_FULL);
        TRS_(0);
        static_for<0, 4>([&](auto Rc) {
            constexpr int R = decltype(Rc)::value;
            if (R % 2 == 0) mbar_wait(bars + 8 * (B_RING_FULL + R / 2), 0);
            fetch_a(R * ROW_BYTES);
            fetch_b(R * ROW_BYTES);
            conv_row<2, 4 - R>(oa, acca, wa, xa);
            conv_row<1, 4 - R>(ob, accb, wb, xb);
        });
        SCHED_FENCE();
        __syncwarp();
        mbar_arrive_if(bars + 8 * (B_RING_EMPTY + lane), lane < 2);
        mbar_wait(bars + 8 * (B_RING_FULL + 2), 0);
        fetch_a(4 * ROW_BYTES);
        fetch_b(4 * ROW_BYTES);
        TRS_(5);
#pragma unroll 1
        for (int k0 = 0; k0 < NT; k0 += 2) {
            const uint32_t ph = (k0 >> 1) & 1;
#pragma unroll
            for (int s = 0; s < 2; s++) {
                const uint32_t dst = s * STG_BYTES;
#pragma unroll
                for (int R = 0; R < 4; R++) {
                    const int nrow = (4 * (s ^ 1) + R + 1) & 7;
                    conv_row<2, 0>(oa, acca, wa, xa);
                    if (R == 0) mbar_wait(bars + 8 * (B_STG_EMPTY + s), ph ^ 1);
                    if (R & 1) mbar_wait(bars + 8 * (B_RING_FULL + nrow / 2), (s == 0 && R == 1) ? ph : ph ^ 1);
                    fetch_a(nrow * ROW_BYTES);
                    stsm4(stg_a + dst + R * (BW * STG_PITCH), oa[0], oa[1], oa[2], oa[3]);
                    conv_row<1, 0>(ob, accb, wb, xb);
                    fetch_b(nrow * ROW_BYTES);
                    stsm2(stg_b + dst + R * (BW * STG_PITCH), ob[0], ob[1]);
                    if (R & 1) __syncwarp();
                    if (R == 1) mbar_arrive_if(bars + 8 * (B_RING_EMPTY + 2 * (s ^ 1)), lane == 0);
                    if (R == 3) mbar_arrive_if(arr ^ (16 * s), lane < 2);
                    if (R < 3 || s == 0) SCHED_FENCE();
                }
            }
        }
#pragma unroll
        for (int s = 0; s < 2; s++) {
            mbar_wait(bars + 8 * (B_STG_EMPTY + s), 1);
            mbar_arrive_if(bars + 8 * (B_STG_FULL + 2 * s), lane == 0);
        }
        TRS_(4);
    } else {
        asm volatile("setmaxnreg.inc.sync.aligned.u32 %0;" ::"n"(MLP_REGS));
        TRS_(0);
        {
            const int kk = lane & 7, a0 = (kk + (lane >> 3)) & 7;
#pragma unroll 1
            for (int t = wid; t < 24; t += 8) {
                const uint32_t base = sbase + SM_W1 + (t >> 1) * W1_LBO + (t & 1) * 384;
                uint4 v[6];
                mbar_wait(bars + 8 * (B_WEIGHTS + (t >> 3)), 0);
#pragma unroll
                for (int i = 0; i < 6; i++) v[i] = lds128(base + (i >> 1) * 128 + kk * (HID * 2) + (a0 ^ ((i & 1) * 4)) * 16);
                __syncwarp();
#pragma unroll
                for (int i = 0; i < 6; i++)
                    sts128(base + (i >> 1) * 128 + (a0 ^ ((i & 1) * 4)) * (HID * 2) + kk * 16, bf2h4(v[i]));
            }
            TRS_(1);
            const int q2 = lane & 3, k2 = lane >> 2;
#pragma unroll 1
            for (int t = wid; t < 48; t += 8) {
                const uint32_t base = sbase + SM_W2 + t * W2_KG;
                uint4 v[3];
                mbar_wait(bars + 8 * (B_WEIGHTS + 3 + (t >> 4)), 0);
#pragma unroll
                for (int i = 0; i < 3; i++) v[i] = lds128(base + k2 * (CH * 2) + i * 64 + q2 * 16);
                __syncwarp();
#pragma unroll
                for (int i = 0; i < 3; i++) {
                    const uint32_t d = base + i * 512 + k2 * 16 + q2 * 4;
                    const uint4 c = bf2h4(make_uint4(mulc(v[i].x), mulc(v[i].y), mulc(v[i].z), mulc(v[i].w)));
                    sts32(d, c.x);
                    sts32(d + 128, c.y);
                    sts32(d + 256, c.z);
                    sts32(d + 384, c.w);
                }
            }
            asm volatile("fence.proxy.async.shared::cta;" ::: "memory");
            asm volatile("bar.sync 1, 256;" ::: "memory");
            TRS_(2);
        }

        const uint64_t w1desc = make_desc(sbase + SM_W1, W1_LBO, W1_SBO);
        const uint64_t w2desc = make_desc(sbase + SM_W2, W2_LBO, W2_SBO);
        const uint32_t ldm_addr = sbase + SM_STG + wg * STG_BYTES +
                                  (16 * warp + (lane & 7) + ((lane >> 3) & 1) * 8) * STG_PITCH + (lane >> 4) * 16;
        const uint32_t out_addr = sbase + SM_OUT + wg * OUT_BYTES + (16 * warp + (lane >> 2)) * PXB + (lane & 3) * 16;

        uint32_t a[6][4], r[6][4];
        uint32_t h[2][24], acc2[24];
        uint32_t p[24][4], u[2][4];
        uint16_t tl[2][4], tg[2][4];
        uint32_t ps[2], sq[4], rp[2], cp[2], st[2], sx[2];
        auto fence_regs = [&](auto& v) {
#pragma unroll
            for (int i = 0; i < (int)(sizeof(v) / 4); i++) asm volatile("" : "+r"(v[i]) :: "memory");
        };
#pragma unroll
        for (int i = 0; i < 24; i++) acc2[i] = h[0][i] = h[1][i] = 0u;
        fence_regs(acc2);
        fence_regs(h[0]);
        fence_regs(h[1]);

        auto layernorm = [&](auto Tc) {
            constexpr int t = decltype(Tc)::value;
            if constexpr (t == SG_LD || t == SG_LD + 1) {
#pragma unroll
                for (int ks = 3 * (t - SG_LD); ks < 3 * (t - SG_LD) + 3; ks++)
                    ldsm4(r[ks][0], r[ks][1], r[ks][2], r[ks][3], ldm_addr + ks * 32);
            }
            if constexpr (t >= SG_S0 && t <= SG_SUM) {
                constexpr int k0 = 2 * (t - SG_S0);
#pragma unroll
                for (int j = 0; j < 2; j++) {
                    const uint32_t v = hadd2(hadd2(r[k0][j], r[k0][j + 2]), hadd2(r[k0 + 1][j], r[k0 + 1][j + 2]));
                    ps[j] = k0 == 0 ? v : hadd2(ps[j], v);
                }
#pragma unroll
                for (int ks = k0; ks < k0 + 2; ks++)
#pragma unroll
                    for (int j = 0; j < 4; j++)
                        sq[j] = ks == 0 ? hmul2(r[ks][j], r[ks][j]) : hfma2(r[ks][j], r[ks][j], sq[j]);
            }
            if constexpr (t == SG_SUM) {
                st[0] = fold(ps[0], ps[1]);
                st[1] = fold(hadd2(sq[0], sq[2]), hadd2(sq[1], sq[3]));
#pragma unroll
                for (int i = 0; i < 2; i++) sx[i] = __shfl_xor_sync(0xffffffffu, st[i], 1);
            }
            if constexpr (t == SG_SH2) {
#pragma unroll
                for (int i = 0; i < 2; i++) {
                    st[i] = hadd2(st[i], sx[i]);
                    sx[i] = __shfl_xor_sync(0xffffffffu, st[i], 2);
                }
            }
            if constexpr (t == SG_RS) {
                const uint32_t s1 = hadd2(st[0], sx[0]), s2 = hadd2(st[1], sx[1]);
                float nm[2], var[2];
                bool poor = false;
#pragma unroll
                for (int j = 0; j < 2; j++) {
                    nm[j] = (j ? bf_hi(s1) : bf_lo(s1)) * (-1.0f / CH);
                    const float m2 = nm[j] * nm[j];
                    var[j] = fmaf(j ? bf_hi(s2) : bf_lo(s2), 1.0f / CH, -m2);
                    poor |= !(4.0f * m2 <= var[j]);
                }
                if (__any_sync(0xffffffffu, poor)) {
                    uint32_t d1[4], d2[4];
#pragma unroll
                    for (int j = 0; j < 4; j++) {
                        const uint32_t c = pack_bf16(nm[j & 1], nm[j & 1]);
#pragma unroll
                        for (int ks = 0; ks < 6; ks++) {
                            r[ks][j] = hadd2(r[ks][j], c);
                            d1[j] = ks == 0 ? r[ks][j] : hadd2(d1[j], r[ks][j]);
                            d2[j] = ks == 0 ? hmul2(r[ks][j], r[ks][j]) : hfma2(r[ks][j], r[ks][j], d2[j]);
                        }
                    }
                    uint32_t v1 = fold(hadd2(d1[0], d1[2]), hadd2(d1[1], d1[3]));
                    uint32_t v2 = fold(hadd2(d2[0], d2[2]), hadd2(d2[1], d2[3]));
#pragma unroll
                    for (int i = 1; i <= 2; i++) {
                        v1 = hadd2(v1, __shfl_xor_sync(0xffffffffu, v1, i));
                        v2 = hadd2(v2, __shfl_xor_sync(0xffffffffu, v2, i));
                    }
#pragma unroll
                    for (int j = 0; j < 2; j++) {
                        nm[j] = (j ? bf_hi(v1) : bf_lo(v1)) * (-1.0f / CH);
                        var[j] = fmaxf(fmaf(j ? bf_hi(v2) : bf_lo(v2), 1.0f / CH, -nm[j] * nm[j]), 0.f);
                    }
                }
#pragma unroll
                for (int j = 0; j < 2; j++) {
                    constexpr float K = 1.0f / (GELU_S * GELU_S);
                    float rs;
                    asm("rsqrt.approx.ftz.f32 %0, %1;" : "=f"(rs) : "f"(fmaf(var[j], K, K * 1e-5f)));
                    rp[j] = pack_bf16(rs, rs);
                    const float c = nm[j] * bf_lo(rp[j]);
                    cp[j] = pack_bf16(c, c);
                }
            }
            if constexpr (t >= SG_CVT && t < SG_CVT + 3) {
#pragma unroll
                for (int ks = 2 * (t - SG_CVT); ks < 2 * (t - SG_CVT) + 2; ks++)
#pragma unroll
                    for (int j = 0; j < 4; j++) a[ks][j] = bf2h(hfma2(r[ks][j], rp[j & 1], cp[j & 1]));
            }
        };
        auto gelu = [&](auto Tc) {
            constexpr int t = decltype(Tc)::value;
            constexpr int sf = (t + 1) % 24, sb = (t + 23) % 24;
            if constexpr (t >= 0) {
#pragma unroll
                for (int i = 0; i < 4; i++) gelu_tanh(tl[t & 1][i], tg[t & 1][i], u[t & 1][i]);
            }
#pragma unroll
            for (int i = 0; i < 4; i++) u[(t + 1) & 1][i] = gelu_front(h[(sf / 6) & 1][4 * (sf % 6) + i]);
            if constexpr (t >= 1) {
#pragma unroll
                for (int i = 0; i < 4; i++)
                    p[sb][i] = gelu_back(h[(sb / 6) & 1][4 * (sb % 6) + i], tl[(t + 1) & 1][i], tg[(t + 1) & 1][i]);
            }
        };
        auto arrive = [&](int bar) {
            __syncwarp();
            mbar_arrive_if(bars + 8 * (bar + wg), lane == 0);
        };
        auto store_out = [&](int i) {
            const int half = i / 3, j = i % 3;
            sts128(out_addr + half * 8 * PXB + j * 64,
                   make_uint4(h2bf(acc2[8 * j + half]), h2bf(acc2[8 * j + 2 + half]), h2bf(acc2[8 * j + 4 + half]),
                              h2bf(acc2[8 * j + 6 + half])));
        };
        auto out_ready = [&](bool pred) {
            asm volatile("fence.proxy.async.shared::cta;" ::: "memory");
            __syncwarp();
            mbar_arrive_if(bars + 8 * (B_OUT_READY + wg), pred && lane == 0);
        };

        mbar_wait(bars + 8 * (B_STG_FULL + 2 * wg), 0);
        TRS_(3);
        static_for<SG_LD, SG_CVT + 3>(layernorm);
        SCHED_FENCE();
        arrive(B_STG_EMPTY);
        WG_FENCE();
#pragma unroll
        for (int ks = 0; ks < 6; ks++) gemm1_step(h[0], a, w1desc, 0, ks);
        WG_COMMIT();
#pragma unroll
        for (int ks = 0; ks < 6; ks++) gemm1_step(h[1], a, w1desc, 1, ks);
        WG_COMMIT();
        wg_wait<1>();
        fence_regs(h[0]);
        static_for<-1, 5>(gelu);
        wg_wait<0>();

#pragma unroll 1
        for (int it = 0;; it++) {
            bool done = false;
            static_for<5, 29>([&](auto Tc) {
                constexpr int t = decltype(Tc)::value;
                if (done) return;
                if constexpr (t == 5) {
                    wg_wait<0>();
                    fence_regs(h[0]);
                } else if constexpr (t % 6 == 5) {
                    wg_wait<1>();
                } else if constexpr (t == SG_EPI) {
                    wg_wait<2>();
                    fence_regs(acc2);
                }
                if constexpr (t % 6 == 5) fence_regs(h[((t + 1) / 6) & 1]);
                if constexpr (t == SG_LD) mbar_wait(bars + 8 * (B_STG_FULL + 2 * wg), (it + 1) & 1);
                if constexpr (t == SG_OUT) out_ready(it > 0);
                if constexpr (t == SG_SUM + 1) arrive(B_STG_EMPTY);
                if constexpr (t == SG_EPI) {
                    mbar_wait(bars + 8 * (B_OUT_FREE + wg), (it & 1) ^ 1);
                    if (it == NT / 2 - 1) { done = true; return; }
                }
                constexpr bool g1seg = t % 6 >= 1 && t % 6 <= 3;
                if constexpr (t <= 25 || g1seg) {
                    WG_FENCE();
                    if constexpr (t <= 25) {
#pragma unroll
                        for (int j = (t == 5 ? 0 : t - 2); j <= t - 2; j++) gemm2_step(acc2, p[j], w2desc, j);
                    }
                    if constexpr (g1seg) {
                        if constexpr (t == 25) WG_COMMIT();
                        constexpr int c = (t / 6 + 1) % 4;
                        gemm1_step(h[c & 1], a, w1desc, c, (t % 6 - 1) * 2);
                        gemm1_step(h[c & 1], a, w1desc, c, (t % 6 - 1) * 2 + 1);
                    }
                    WG_COMMIT();
                }
                gelu(Tc);
                if constexpr (t >= SG_EPI) {
#pragma unroll
                    for (int i = 3 * (t - SG_EPI); i < 3 * (t - SG_EPI) + 3; i++) store_out(i);
                }
                layernorm(Tc);
                SCHED_FENCE();
            });
            if (done) break;
            wg_wait<0>();
        }
        wg_wait<0>();
        fence_regs(acc2);
#pragma unroll
        for (int i = 0; i < 6; i++) store_out(i);
        out_ready(true);
        TRS_(4);
    }
}

typedef CUresult (*PFN_encodeTiled)(CUtensorMap*, CUtensorMapDataType, cuuint32_t, void*, const cuuint64_t*,
                                    const cuuint64_t*, const cuuint32_t*, const cuuint32_t*, CUtensorMapInterleave,
                                    CUtensorMapSwizzle, CUtensorMapL2promotion, CUtensorMapFloatOOBfill);

}

extern "C" void kernel_launch(void* const* d_in, const int* in_sizes, int n_in, void* d_out, int out_size) {
    const __nv_bfloat16* x = (const __nv_bfloat16*)d_in[0];
    const __nv_bfloat16* dwl = (const __nv_bfloat16*)d_in[1];
    const __nv_bfloat16* dws = (const __nv_bfloat16*)d_in[2];
    const __nv_bfloat16* w1 = (const __nv_bfloat16*)d_in[3];
    const __nv_bfloat16* w2 = (const __nv_bfloat16*)d_in[4];

    static PFN_encodeTiled encode = nullptr;
    if (!encode) {
        void* fn = nullptr;
        cudaDriverEntryPointQueryResult qres;
        cudaGetDriverEntryPoint("cuTensorMapEncodeTiled", &fn, cudaEnableDefault, &qres);
        encode = (PFN_encodeTiled)fn;
        cudaFuncSetAttribute(fused_block_kernel, cudaFuncAttributeMaxDynamicSharedMemorySize, SMEM_TOTAL);
    }
    CUtensorMap rowmap, copymap, outmap;
    cuuint64_t gdim[3] = {(cuuint64_t)CH, (cuuint64_t)IMG_W, (cuuint64_t)IMG_H};
    cuuint64_t gstride[2] = {(cuuint64_t)PXB, (cuuint64_t)IMG_W * PXB};
    cuuint32_t estr[4] = {1, 1, 1, 1};
    cuuint32_t box_row[3] = {(cuuint32_t)CH, (cuuint32_t)ROW_PX, 2};
    cuuint32_t box_tile[3] = {(cuuint32_t)CH, (cuuint32_t)BW, (cuuint32_t)TR};
    encode(&rowmap, CU_TENSOR_MAP_DATA_TYPE_BFLOAT16, 3, (void*)x, gdim, gstride, box_row, estr,
           CU_TENSOR_MAP_INTERLEAVE_NONE, CU_TENSOR_MAP_SWIZZLE_NONE, CU_TENSOR_MAP_L2_PROMOTION_L2_256B,
           CU_TENSOR_MAP_FLOAT_OOB_FILL_NONE);
    cuuint64_t cdim[4] = {(cuuint64_t)CH, (cuuint64_t)BW, (cuuint64_t)(IMG_W / BW), (cuuint64_t)IMG_H};
    cuuint64_t cstride[3] = {(cuuint64_t)PXB, (cuuint64_t)BW * PXB, (cuuint64_t)IMG_W * PXB};
    cuuint32_t box_copy[4] = {(cuuint32_t)CH, (cuuint32_t)ROW_PX, 1, 2};
    encode(&copymap, CU_TENSOR_MAP_DATA_TYPE_BFLOAT16, 4, d_out, cdim, cstride, box_copy, estr,
           CU_TENSOR_MAP_INTERLEAVE_NONE, CU_TENSOR_MAP_SWIZZLE_NONE, CU_TENSOR_MAP_L2_PROMOTION_NONE,
           CU_TENSOR_MAP_FLOAT_OOB_FILL_NONE);
    encode(&outmap, CU_TENSOR_MAP_DATA_TYPE_BFLOAT16, 3, d_out, gdim, gstride, box_tile, estr,
           CU_TENSOR_MAP_INTERLEAVE_NONE, CU_TENSOR_MAP_SWIZZLE_NONE, CU_TENSOR_MAP_L2_PROMOTION_NONE,
           CU_TENSOR_MAP_FLOAT_OOB_FILL_NONE);
    fused_block_kernel<<<NCTA, NTHREADS, SMEM_TOTAL>>>(rowmap, copymap, outmap, dwl, dws, w1, w2);
}
```

```cpp
#include <cuda_runtime.h>
#include <cuda_bf16.h>
#include <cuda.h>
#include <stdint.h>
#include <type_traits>

#define TRS_(i)

namespace {

constexpr int IMG_H = 512, IMG_W = 512, CH = 96, HID = 384;
constexpr int BW = 16;
constexpr int TR = 4;
constexpr int NT = 32;
constexpr int NCTA = (IMG_W / BW) * (IMG_H / (TR * NT));
constexpr int PXB = CH * 2;
constexpr int ROW_PX = BW + 4;
constexpr int ROW_BYTES = ROW_PX * PXB;
constexpr int UNIT_BYTES = 2 * ROW_BYTES;
constexpr int NU = 2 * NT + 2;
constexpr int STG_PITCH = 208;
constexpr int STG_BYTES = 64 * STG_PITCH;
constexpr int OUT_BYTES = 64 * PXB;
constexpr int NTHREADS = 512;
constexpr int MLP_REGS = 168, TMA_REGS = 24, CONV_REGS = 512 - 2 * MLP_REGS - TMA_REGS;

constexpr int W1_BYTES = CH * HID * 2;
constexpr int W2_BYTES = HID * CH * 2;
constexpr int WPIECE = 24576;
constexpr int SM_W1 = 0;
constexpr int SM_W2 = SM_W1 + W1_BYTES;
constexpr int SM_RING = SM_W2 + W2_BYTES;
constexpr int SM_OUT = SM_RING + 4 * UNIT_BYTES;
constexpr int SM_STG = SM_OUT + 2 * OUT_BYTES;
constexpr int SM_BAR = SM_STG + 2 * STG_BYTES;
constexpr int SMEM_TOTAL = SM_BAR + 256;
static_assert(SMEM_TOTAL <= 232448, "smem");

constexpr int B_RING_FULL = 0;
constexpr int B_RING_EMPTY = 4;
constexpr int B_STG_FULL = 8;
constexpr int B_STG_EMPTY = 12;
constexpr int B_OUT_READY = 14;
constexpr int B_OUT_FREE = 16;
constexpr int B_COPIED = 18;
constexpr int B_FILTER = 19;
constexpr int B_WEIGHTS = 20;
constexpr int B_BASE = 26;

constexpr int W1_LBO = 8 * HID * 2, W1_SBO = 128;
constexpr int W2_KG = 8 * CH * 2;
constexpr int W2_LBO = 8 * W2_KG, W2_SBO = 128;

constexpr float GELU_S = 0.3292034911525734f;
constexpr uint32_t GELU_CH2 = 0x3FC23FC2u, GELU_CL2 = 0x3B513B51u;
constexpr uint32_t GELU_A2 = 0x40D940D9u;

__device__ __forceinline__ uint32_t smem_u32(const void* p) {
    return (uint32_t)__cvta_generic_to_shared(p);
}
__device__ __forceinline__ uint64_t make_desc(uint32_t addr, uint32_t lbo, uint32_t sbo) {
    return (uint64_t)((addr & 0x3FFFF) >> 4) | ((uint64_t)(lbo >> 4) << 16) | ((uint64_t)(sbo >> 4) << 32);
}
__device__ __forceinline__ void mbar_init(uint32_t bar, uint32_t cnt) {
    asm volatile("mbarrier.init.shared::cta.b64 [%0], %1;" ::"r"(bar), "r"(cnt));
}
__device__ __forceinline__ void mbar_expect_tx(uint32_t bar, uint32_t bytes) {
    asm volatile("mbarrier.arrive.expect_tx.shared::cta.b64 _, [%0], %1;" ::"r"(bar), "r"(bytes) : "memory");
}
__device__ __forceinline__ void mbar_arrive_if(uint32_t bar, bool pred) {
    asm volatile("{\n.reg .pred p;\nsetp.ne.u32 p, %1, 0;\n@p mbarrier.arrive.shared::cta.b64 _, [%0];\n}\n"
                 ::"r"(bar), "r"((uint32_t)pred) : "memory");
}
__device__ __forceinline__ void mbar_wait(uint32_t bar, uint32_t parity) {
    asm volatile(
        "{\n"
        ".reg .pred p;\n"
        "WAIT_LOOP:\n"
        "mbarrier.try_wait.parity.shared::cta.b64 p, [%0], %1, %2;\n"
        "@p bra WAIT_DONE;\n"
        "bra WAIT_LOOP;\n"
        "WAIT_DONE:\n"
        "}\n" ::"r"(bar), "r"(parity), "r"(20000) : "memory");
}
__device__ __forceinline__ void tma_load3d(uint32_t dst, const CUtensorMap* map, int cx, int cy, uint32_t bar) {
    asm volatile(
        "cp.async.bulk.tensor.3d.shared::cluster.global.mbarrier::complete_tx::bytes [%0], [%1, {%2, %3, %4}], [%5];"
        ::"r"(dst), "l"((uint64_t)map), "r"(0), "r"(cx), "r"(cy), "r"(bar) : "memory");
}
__device__ __forceinline__ void bulk_load(uint32_t dst, const void* src, uint32_t bytes, uint32_t bar) {
    asm volatile("cp.async.bulk.shared::cluster.global.mbarrier::complete_tx::bytes [%0], [%1], %2, [%3];"
                 ::"r"(dst), "l"(src), "r"(bytes), "r"(bar) : "memory");
}
__device__ __forceinline__ uint4 lds128(uint32_t addr) {
    uint4 v;
    asm volatile("ld.shared.v4.u32 {%0,%1,%2,%3}, [%4];" : "=r"(v.x), "=r"(v.y), "=r"(v.z), "=r"(v.w) : "r"(addr));
    return v;
}
__device__ __forceinline__ uint32_t lds32(uint32_t addr) {
    uint32_t v;
    asm volatile("ld.shared.u32 %0, [%1];" : "=r"(v) : "r"(addr));
    return v;
}
__device__ __forceinline__ void sts128(uint32_t addr, uint4 v) {
    asm volatile("st.shared.v4.u32 [%0], {%1,%2,%3,%4};" ::"r"(addr), "r"(v.x), "r"(v.y), "r"(v.z), "r"(v.w) : "memory");
}
__device__ __forceinline__ void sts32(uint32_t addr, uint32_t a) {
    asm volatile("st.shared.u32 [%0], %1;" ::"r"(addr), "r"(a) : "memory");
}
__device__ __forceinline__ void ldsm4(uint32_t& a, uint32_t& b, uint32_t& c, uint32_t& d, uint32_t addr) {
    asm volatile("ldmatrix.sync.aligned.m8n8.x4.shared.b16 {%0,%1,%2,%3}, [%4];"
                 : "=r"(a), "=r"(b), "=r"(c), "=r"(d) : "r"(addr));
}
__device__ __forceinline__ void ldsm2(uint32_t& a, uint32_t& b, uint32_t addr) {
    asm volatile("ldmatrix.sync.aligned.m8n8.x2.shared.b16 {%0,%1}, [%2];" : "=r"(a), "=r"(b) : "r"(addr));
}
__device__ __forceinline__ void stsm4(uint32_t addr, uint32_t a, uint32_t b, uint32_t c, uint32_t d) {
    asm volatile("stmatrix.sync.aligned.m8n8.x4.shared.b16 [%0], {%1,%2,%3,%4};"
                 ::"r"(addr), "r"(a), "r"(b), "r"(c), "r"(d) : "memory");
}
__device__ __forceinline__ void stsm2(uint32_t addr, uint32_t a, uint32_t b) {
    asm volatile("stmatrix.sync.aligned.m8n8.x2.shared.b16 [%0], {%1,%2};" ::"r"(addr), "r"(a), "r"(b) : "memory");
}
__device__ __forceinline__ uint32_t hfma2(uint32_t a, uint32_t b, uint32_t c) {
    uint32_t d;
    asm("fma.rn.bf16x2 %0, %1, %2, %3;" : "=r"(d) : "r"(a), "r"(b), "r"(c));
    return d;
}
__device__ __forceinline__ uint32_t hmul2(uint32_t a, uint32_t b) {
    uint32_t d;
    asm("mul.rn.bf16x2 %0, %1, %2;" : "=r"(d) : "r"(a), "r"(b));
    return d;
}
__device__ __forceinline__ uint32_t hadd2(uint32_t a, uint32_t b) {
    uint32_t d;
    asm("add.rn.bf16x2 %0, %1, %2;" : "=r"(d) : "r"(a), "r"(b));
    return d;
}
__device__ __forceinline__ uint32_t hsub2(uint32_t a, uint32_t b) {
    uint32_t d;
    asm("sub.rn.bf16x2 %0, %1, %2;" : "=r"(d) : "r"(a), "r"(b));
    return d;
}
__device__ __forceinline__ uint32_t fold(uint32_t a, uint32_t b) {
    return hadd2(__byte_perm(a, b, 0x5410), __byte_perm(a, b, 0x7632));
}
__device__ __forceinline__ float bf_lo(uint32_t v) { return __uint_as_float(v << 16); }
__device__ __forceinline__ float bf_hi(uint32_t v) { return __uint_as_float(v & 0xffff0000u); }
__device__ __forceinline__ uint32_t pack_bf16(float lo, float hi) {
    uint32_t d;
    asm("cvt.rn.bf16x2.f32 %0, %1, %2;" : "=r"(d) : "f"(hi), "f"(lo));
    return d;
}
__device__ __forceinline__ uint32_t pack_f16(float lo, float hi) {
    uint32_t d;
    asm("cvt.rn.f16x2.f32 %0, %1, %2;" : "=r"(d) : "f"(hi), "f"(lo));
    return d;
}
__device__ __forceinline__ uint32_t bf2h(uint32_t v) { return pack_f16(bf_lo(v), bf_hi(v)); }
__device__ __forceinline__ uint4 bf2h4(uint4 v) { return make_uint4(bf2h(v.x), bf2h(v.y), bf2h(v.z), bf2h(v.w)); }
__device__ __forceinline__ uint32_t mulc(uint32_t v) { return hfma2(v, GELU_CH2, hmul2(v, GELU_CL2)); }
__device__ __forceinline__ uint32_t h2bf(uint32_t h) {
    float lo, hi;
    asm("{\n.reg .b16 l, h;\nmov.b32 {l, h}, %2;\ncvt.f32.f16 %0, l;\ncvt.f32.f16 %1, h;\n}\n" : "=f"(lo), "=f"(hi) : "r"(h));
    return pack_bf16(lo, hi);
}

#define WG_FENCE() asm volatile("wgmma.fence.sync.aligned;" ::: "memory")
#define WG_COMMIT() asm volatile("wgmma.commit_group.sync.aligned;" ::: "memory")
template <int N>
__device__ __forceinline__ void wg_wait() {
    asm volatile("wgmma.wait_group.sync.aligned %0;" ::"n"(N) : "memory");
}
#define SCHED_FENCE() asm volatile("pmevent.mask 0;" ::: "memory")

template <bool ACC>
__device__ __forceinline__ void wgmma_rs(uint32_t (&d)[24], const uint32_t (&a)[4], uint64_t desc) {
    asm volatile(
        "{\n"
        ".reg .pred p;\n"
        "setp.ne.b32 p, %29, 0;\n"
        "wgmma.mma_async.sync.aligned.m64n96k16.f16.f16.f16 {"
        "%0,%1,%2,%3,%4,%5,%6,%7,%8,%9,%10,%11,%12,%13,%14,%15,"
        "%16,%17,%18,%19,%20,%21,%22,%23"
        "}, {%24,%25,%26,%27}, %28, p, 1, 1, 1;\n"
        "}\n"
        : "+r"(d[0]), "+r"(d[1]), "+r"(d[2]), "+r"(d[3]), "+r"(d[4]), "+r"(d[5]), "+r"(d[6]), "+r"(d[7]),
          "+r"(d[8]), "+r"(d[9]), "+r"(d[10]), "+r"(d[11]), "+r"(d[12]), "+r"(d[13]), "+r"(d[14]), "+r"(d[15]),
          "+r"(d[16]), "+r"(d[17]), "+r"(d[18]), "+r"(d[19]), "+r"(d[20]), "+r"(d[21]), "+r"(d[22]), "+r"(d[23])
        : "r"(a[0]), "r"(a[1]), "r"(a[2]), "r"(a[3]), "l"(desc), "n"(ACC ? 1 : 0));
}
__device__ __forceinline__ void gemm1_step(uint32_t (&h)[24], const uint32_t (&a)[6][4], uint64_t w1desc, int c, int ks) {
    const uint64_t d = w1desc + (uint64_t)((c * 12 * W1_SBO + ks * 2 * W1_LBO) >> 4);
    if (ks == 0) wgmma_rs<false>(h, a[0], d);
    else wgmma_rs<true>(h, a[ks], d);
}
__device__ __forceinline__ void gemm2_step(uint32_t (&acc2)[24], const uint32_t (&p)[4], uint64_t w2desc, int j) {
    const uint64_t d = w2desc + (uint64_t)(((16 * (j % 3) + j / 3) * W2_KG) >> 4);
    if (j == 0) wgmma_rs<false>(acc2, p, d);
    else wgmma_rs<true>(acc2, p, d);
}
__device__ __forceinline__ uint32_t gelu_front(uint32_t y) {
    uint32_t t, u;
    asm("fma.rn.f16x2 %0, %1, %1, %2;" : "=r"(t) : "r"(y), "r"(GELU_A2));
    asm("mul.rn.f16x2 %0, %1, %2;" : "=r"(u) : "r"(y), "r"(t));
    return u;
}
__device__ __forceinline__ void gelu_tanh(uint16_t& lo, uint16_t& hi, uint32_t u) {
    asm("{\n.reg .b16 l, h;\nmov.b32 {l, h}, %2;\ntanh.approx.f16 %0, l;\ntanh.approx.f16 %1, h;\n}\n"
        : "=h"(lo), "=h"(hi) : "r"(u));
}
__device__ __forceinline__ uint32_t gelu_back(uint32_t y, uint16_t lo, uint16_t hi) {
    uint32_t g;
    asm("{\n.reg .b32 t;\nmov.b32 t, {%2, %3};\nfma.rn.f16x2 %0, %1, t, %1;\n}\n" : "=r"(g) : "r"(y), "h"(lo), "h"(hi));
    return g;
}

template <int B, int E, typename F>
__device__ __forceinline__ void static_for(F&& f) {
    if constexpr (B < E) {
        f(std::integral_constant<int, B>{});
        static_for<B + 1, E>(f);
    }
}

template <int NP, int R0, int R1 = 5>
__device__ __forceinline__ void conv_row(uint32_t (&o)[2 * NP], uint32_t (&acc)[4][NP][3], const uint32_t (&w)[5][7],
                                         const uint32_t (&x)[2 * NP + 4]) {
    uint32_t e[NP + 1], f[NP + 1], t[5][NP][3];
#pragma unroll
    for (int i = 0; i <= NP; i++) {
        e[i] = hsub2(x[2 * i], x[2 * i + 1]);
        f[i] = hsub2(x[2 * i + 2], x[2 * i + 1]);
    }
#pragma unroll
    for (int p = 0; p < NP; p++) {
#pragma unroll
        for (int r = R0; r < R1; r++) {
            const uint32_t(&h)[7] = w[4 - r];
            t[r][p][1] = r < 4 ? hfma2(x[2 * p + 1], h[3], acc[r & 3][p][1]) : hmul2(x[2 * p + 1], h[3]);
            t[r][p][0] = r < 4 ? hfma2(x[2 * p + 4], h[2], acc[r & 3][p][0]) : hmul2(x[2 * p + 4], h[2]);
            t[r][p][2] = r < 4 ? hfma2(x[2 * p + 5], h[2], acc[r & 3][p][2]) : hmul2(x[2 * p + 5], h[2]);
        }
#pragma unroll
        for (int r = R0; r < R1; r++) {
            const uint32_t(&h)[7] = w[4 - r];
            t[r][p][1] = hfma2(x[2 * p + 3], h[4], t[r][p][1]);
            t[r][p][0] = hfma2(e[p], h[0], t[r][p][0]);
            t[r][p][2] = hfma2(f[p], h[5], t[r][p][2]);
        }
#pragma unroll
        for (int r = R0; r < R1; r++) {
            const uint32_t(&h)[7] = w[4 - r];
            t[r][p][0] = hfma2(e[p + 1], h[1], t[r][p][0]);
            t[r][p][2] = hfma2(f[p + 1], h[6], t[r][p][2]);
        }
        if (R0 == 0) {
            o[2 * p] = hadd2(t[0][p][0], t[0][p][1]);
            o[2 * p + 1] = hadd2(t[0][p][1], t[0][p][2]);
        }
#pragma unroll
        for (int r = (R0 > 0 ? R0 : 1); r < R1; r++)
#pragma unroll
            for (int m = 0; m < 3; m++) acc[r - 1][p][m] = t[r][p][m];
    }
}

constexpr int SG_LD = 11, SG_S0 = 12, SG_SUM = 14, SG_SH2 = 15, SG_RS = 16, SG_CVT = 18;
constexpr int SG_OUT = 6;
constexpr int SG_EPI = 27;

__global__ void __launch_bounds__(NTHREADS, 1)
fused_block_kernel(const __grid_constant__ CUtensorMap rowmap, const __grid_constant__ CUtensorMap copymap,
                   const __grid_constant__ CUtensorMap outmap,
                   const __nv_bfloat16* __restrict__ dwl, const __nv_bfloat16* __restrict__ dws,
                   const __nv_bfloat16* __restrict__ w1, const __nv_bfloat16* __restrict__ w2) {
    extern __shared__ __align__(1024) uint8_t smem[];
    const uint32_t sbase = smem_u32(smem);
    const int tid = threadIdx.x;
    const int wid = __shfl_sync(0xffffffffu, tid >> 5, 0);
    const int wg = wid >> 2, warp = wid & 3;
    const int lane = tid & 31;
    const uint32_t bars = sbase + SM_BAR;
    const int x0 = (blockIdx.x >> 2) * BW, y0 = (blockIdx.x & 3) * (TR * NT);

    if (tid == NTHREADS - 128) {
        const char* w1b = reinterpret_cast<const char*>(w1);
        const char* w2b = reinterpret_cast<const char*>(w2);
        asm volatile("cp.async.bulk.prefetch.L2.global [%0], %1;"
                     ::"l"(((blockIdx.x & 1) ? w2b : w1b) + (blockIdx.x >> 1) * (W1_BYTES / (NCTA / 2))), "r"(W1_BYTES / (NCTA / 2))
                     : "memory");
        mbar_init(bars + 8 * B_FILTER, 1);
#pragma unroll
        for (int i = 0; i < 4; i++) mbar_init(bars + 8 * (B_RING_FULL + i), 1);
#pragma unroll
        for (int i = 0; i < 6; i++) mbar_init(bars + 8 * (B_WEIGHTS + i), 1);
        asm volatile("fence.mbarrier_init.release.cluster;" ::: "memory");
        mbar_expect_tx(bars + 8 * B_FILTER, 34 * PXB);
        bulk_load(sbase + SM_OUT, dws, 25 * PXB, bars + 8 * B_FILTER);
        bulk_load(sbase + SM_OUT + 25 * PXB, dwl, 9 * PXB, bars + 8 * B_FILTER);
#pragma unroll
        for (int i = 0; i < 6; i++) {
            if (i < 2) {
#pragma unroll
                for (int u = 2 * i; u < 2 * i + 2; u++) {
                    mbar_expect_tx(bars + 8 * (B_RING_FULL + u), UNIT_BYTES);
                    tma_load3d(sbase + SM_RING + u * UNIT_BYTES, &rowmap, x0 - 2, y0 - 2 + 2 * u, bars + 8 * (B_RING_FULL + u));
                }
            }
            mbar_expect_tx(bars + 8 * (B_WEIGHTS + i), WPIECE);
            bulk_load(sbase + i * WPIECE, (i < 3 ? w1b : w2b) + (i % 3) * WPIECE, WPIECE, bars + 8 * (B_WEIGHTS + i));
        }
    } else if (tid == NTHREADS - 96) {
#pragma unroll
        for (int m = 0; m < 2; m++) {
            mbar_init(bars + 8 * (B_RING_EMPTY + 2 * m), 4);
            mbar_init(bars + 8 * (B_RING_EMPTY + 2 * m + 1), 4);
            mbar_init(bars + 8 * (B_STG_FULL + 2 * m), 4);
            mbar_init(bars + 8 * (B_STG_EMPTY + m), 4);
            mbar_init(bars + 8 * (B_OUT_READY + m), 4);
            mbar_init(bars + 8 * (B_OUT_FREE + m), 1);
        }
        mbar_init(bars + 8 * B_COPIED, 2);
        sts32(bars + 8 * B_BASE, sbase);
        asm volatile("fence.mbarrier_init.release.cluster;" ::: "memory");
    }
    __syncthreads();

    if (wg == 3) {
        asm volatile("setmaxnreg.dec.sync.aligned.u32 %0;" ::"n"(TMA_REGS));
        const int m = warp >> 1;
        if (lane == 0) {
            if (warp == 0 || warp == 3) {
#pragma unroll 1
                for (int u = 2 * m; u < NU - 1; u += (u & 1) ? 3 : 1) {
                    const uint32_t fb = bars + 8 * (B_RING_FULL + (u & 3)), buf = sbase + SM_RING + (u & 3) * UNIT_BYTES;
                    mbar_wait(bars + 8 * (B_RING_EMPTY + (u & 3)), (u >> 2) & 1);
                    if (u != 0) {
                        asm volatile("cp.async.bulk.tensor.4d.global.shared::cta.bulk_group [%0, {%1, %2, %3, %4}], [%5];"
                                     ::"l"((uint64_t)&copymap), "r"(0), "r"(0), "r"(blockIdx.x >> 2), "r"(y0 - 2 + 2 * u),
                                     "r"(buf + 2 * PXB) : "memory");
                        asm volatile("cp.async.bulk.commit_group;" ::: "memory");
                        asm volatile("cp.async.bulk.wait_group 0;" ::: "memory");
                    }
                    if (u + 4 < NU) {
                        mbar_expect_tx(fb, UNIT_BYTES);
                        tma_load3d(buf, &rowmap, x0 - 2, y0 + 6 + 2 * u, fb);
                    }
                }
                mbar_arrive_if(bars + 8 * B_COPIED, true);
            } else {
                const uint32_t buf = sbase + SM_OUT + m * OUT_BYTES;
#pragma unroll 1
                for (int i = 0; i < NT / 2; i++) {
                    if (i == NT / 2 - 1) mbar_wait(bars + 8 * B_COPIED, 0);
                    mbar_wait(bars + 8 * (B_OUT_READY + m), i & 1);
                    asm volatile("cp.reduce.async.bulk.tensor.3d.global.shared::cta.add.bulk_group [%0, {%1, %2, %3}], [%4];"
                                 ::"l"((uint64_t)&outmap), "r"(0), "r"(x0), "r"(y0 + TR * (2 * i + m)), "r"(buf) : "memory");
                    asm volatile("cp.async.bulk.commit_group;" ::: "memory");
                    asm volatile("cp.async.bulk.wait_group 0;" ::: "memory");
                    mbar_arrive_if(bars + 8 * (B_OUT_FREE + m), true);
                }
            }
        }
    } else if (wg == 2) {
        asm volatile("setmaxnreg.inc.sync.aligned.u32 %0;" ::"n"(CONV_REGS));
        uint32_t wa[5][7], wb[5][7];
        {
            const uint32_t pa = sbase + SM_OUT + 4 * lane, pb = sbase + SM_OUT + 4 * (32 + (lane & 15));
            const bool mir = lane >= 16;
            mbar_wait(bars + 8 * B_FILTER, 0);
#pragma unroll
            for (int r = 0; r < 5; r++) {
                uint32_t u[5], v[5];
#pragma unroll
                for (int c = 0; c < 5; c++) {
                    u[c] = lds32(pa + (5 * r + c) * PXB);
                    v[c] = lds32(pb + (5 * r + c) * PXB);
                    if (r >= 1 && r <= 3 && c >= 1 && c <= 3) {
                        u[c] = hadd2(u[c], lds32(pa + (25 + 3 * (r - 1) + c - 1) * PXB));
                        v[c] = hadd2(v[c], lds32(pb + (25 + 3 * (r - 1) + c - 1) * PXB));
                    }
                }
#pragma unroll
                for (int c = 0; c < 2; c++) {
                    const uint32_t lo = v[c], hi = v[4 - c];
                    v[c] = mir ? hi : lo;
                    v[4 - c] = mir ? lo : hi;
                }
                wa[r][0] = u[0]; wa[r][1] = u[2]; wa[r][2] = u[4]; wa[r][3] = hadd2(u[0], u[1]);
                wa[r][4] = hadd2(u[2], u[3]); wa[r][5] = u[1]; wa[r][6] = u[3];
                wb[r][0] = v[0]; wb[r][1] = v[2]; wb[r][2] = v[4]; wb[r][3] = hadd2(v[0], v[1]);
                wb[r][4] = hadd2(v[2], v[3]); wb[r][5] = v[1]; wb[r][6] = v[3];
            }
        }
        const int mi = lane >> 3, mr = lane & 7, up = mr >> 2;
        const uint32_t ring_a = sbase + SM_RING + (4 * warp + mi) * PXB + mr * 16;
        const uint32_t ring_b0 = sbase + SM_RING + (4 * warp + (up ? 7 - mi : mi)) * PXB + 128 + (mr & 3) * 16;
        const uint32_t ring_b1 = sbase + SM_RING + (4 * warp + (up ? 3 - mi : 4 + mi)) * PXB + 128 + (mr & 3) * 16;
        const uint32_t stg_a = sbase + SM_STG + (4 * warp + mi) * STG_PITCH + mr * 16;
        const uint32_t stg_b = sbase + SM_STG + (4 * warp + (up ? 3 - mi : mi)) * STG_PITCH + 128 + (mr & 3) * 16;
        uint32_t acca[4][2][3], accb[4][1][3], xa[8], xb[6], oa[4], ob[2];
        auto fetch_a = [&](uint32_t off) {
            ldsm4(xa[0], xa[1], xa[2], xa[3], ring_a + off);
            ldsm4(xa[4], xa[5], xa[6], xa[7], ring_a + off + 4 * PXB);
        };
        auto fetch_b = [&](uint32_t off) {
            ldsm4(xb[0], xb[1], xb[2], xb[3], ring_b0 + off);
            ldsm2(xb[4], xb[5], ring_b1 + off);
        };
        const uint32_t arr = bars + 8 * (lane == 0 ? B_RING_EMPTY + 3 : B_STG_FULL);
        TRS_(0);
        static_for<0, 4>([&](auto Rc) {
            constexpr int R = decltype(Rc)::value;
            if (R % 2 == 0) mbar_wait(bars + 8 * (B_RING_FULL + R / 2), 0);
            fetch_a(R * ROW_BYTES);
            fetch_b(R * ROW_BYTES);
            conv_row<2, 4 - R>(oa, acca, wa, xa);
            conv_row<1, 4 - R>(ob, accb, wb, xb);
        });
        SCHED_FENCE();
        __syncwarp();
        mbar_arrive_if(bars + 8 * (B_RING_EMPTY + lane), lane < 2);
        mbar_wait(bars + 8 * (B_RING_FULL + 2), 0);
        fetch_a(4 * ROW_BYTES);
        fetch_b(4 * ROW_BYTES);
        TRS_(5);
        auto tile = [&](auto Sc, auto Lc, uint32_t ph) {
            constexpr int s = decltype(Sc)::value;
            constexpr bool LAST = decltype(Lc)::value;
            static_for<0, 4>([&](auto Rc) {
                constexpr int R = decltype(Rc)::value, R1 = LAST ? 4 - R : 5;
                constexpr int nrow = (4 * (s ^ 1) + R + 1) & 7;
                constexpr bool more = !LAST || R < 3;
                constexpr uint32_t dst = s * STG_BYTES + R * (BW * STG_PITCH);
                conv_row<2, 0, R1>(oa, acca, wa, xa);
                if (R == 0) mbar_wait(bars + 8 * (B_STG_EMPTY + s), ph ^ 1);
                if ((R & 1) && more) mbar_wait(bars + 8 * (B_RING_FULL + nrow / 2), (s == 0 && R == 1) ? ph : ph ^ 1);
                if (more) fetch_a(nrow * ROW_BYTES);
                stsm4(stg_a + dst, oa[0], oa[1], oa[2], oa[3]);
                conv_row<1, 0, R1>(ob, accb, wb, xb);
                if (more) fetch_b(nrow * ROW_BYTES);
                stsm2(stg_b + dst, ob[0], ob[1]);
                if (R & 1) __syncwarp();
                if (R == 1) mbar_arrive_if(bars + 8 * (B_RING_EMPTY + 2 * (s ^ 1)), lane == 0);
                if (R == 3) mbar_arrive_if(arr ^ (16 * s), lane < 2);
                if (R < 3 || s == 0) SCHED_FENCE();
            });
        };
#pragma unroll 1
        for (int k = 0; k < NT / 2 - 1; k++) {
            tile(std::integral_constant<int, 0>{}, std::false_type{}, k & 1);
            tile(std::integral_constant<int, 1>{}, std::false_type{}, k & 1);
        }
        SCHED_FENCE();
        tile(std::integral_constant<int, 0>{}, std::false_type{}, (NT / 2 - 1) & 1);
        tile(std::integral_constant<int, 1>{}, std::true_type{}, (NT / 2 - 1) & 1);
        TRS_(4);
    } else {
        asm volatile("setmaxnreg.inc.sync.aligned.u32 %0;" ::"n"(MLP_REGS));
        TRS_(0);
        {
            const int kk = lane & 7, a0 = (kk + (lane >> 3)) & 7;
#pragma unroll 1
            for (int t = wid; t < 24; t += 8) {
                const uint32_t base = sbase + SM_W1 + (t >> 1) * W1_LBO + (t & 1) * 384;
                uint4 v[6];
                mbar_wait(bars + 8 * (B_WEIGHTS + (t >> 3)), 0);
#pragma unroll
                for (int i = 0; i < 6; i++) v[i] = lds128(base + (i >> 1) * 128 + kk * (HID * 2) + (a0 ^ ((i & 1) * 4)) * 16);
                __syncwarp();
#pragma unroll
                for (int i = 0; i < 6; i++)
                    sts128(base + (i >> 1) * 128 + (a0 ^ ((i & 1) * 4)) * (HID * 2) + kk * 16, bf2h4(v[i]));
            }
            TRS_(1);
            const int q2 = lane & 3, k2 = lane >> 2;
#pragma unroll 1
            for (int t = wid; t < 48; t += 8) {
                const uint32_t base = sbase + SM_W2 + t * W2_KG;
                uint4 v[3];
                mbar_wait(bars + 8 * (B_WEIGHTS + 3 + (t >> 4)), 0);
#pragma unroll
                for (int i = 0; i < 3; i++) v[i] = lds128(base + k2 * (CH * 2) + i * 64 + q2 * 16);
                __syncwarp();
#pragma unroll
                for (int i = 0; i < 3; i++) {
                    const uint32_t d = base + i * 512 + k2 * 16 + q2 * 4;
                    const uint4 c = bf2h4(make_uint4(mulc(v[i].x), mulc(v[i].y), mulc(v[i].z), mulc(v[i].w)));
                    sts32(d, c.x);
                    sts32(d + 128, c.y);
                    sts32(d + 256, c.z);
                    sts32(d + 384, c.w);
                }
            }
            asm volatile("fence.proxy.async.shared::cta;" ::: "memory");
            asm volatile("bar.sync 1, 256;" ::: "memory");
            TRS_(2);
        }

        uint64_t w1desc = make_desc(sbase + SM_W1, W1_LBO, W1_SBO);
        uint64_t w2desc = make_desc(sbase + SM_W2, W2_LBO, W2_SBO);
        const uint32_t ldm_addr = sbase + SM_STG + wg * STG_BYTES +
                                  (16 * warp + (lane & 7) + ((lane >> 3) & 1) * 8) * STG_PITCH + (lane >> 4) * 16;
        const uint32_t out_addr = sbase + SM_OUT + wg * OUT_BYTES + (16 * warp + (lane >> 2)) * PXB + (lane & 3) * 16;

        uint32_t a[6][4], r[6][4];
        uint32_t h[2][24], acc2[24];
        uint32_t p[24][4], u[2][4];
        uint16_t tl[2][4], tg[2][4];
        uint32_t ps[2], sq[4], rp[2], cp[2], st[2], sx[2];
        auto fence_regs = [&](auto& v) {
#pragma unroll
            for (int i = 0; i < (int)(sizeof(v) / 4); i++) asm volatile("" : "+r"(v[i]) :: "memory");
        };
#pragma unroll
        for (int i = 0; i < 24; i++) acc2[i] = h[0][i] = h[1][i] = 0u;
        fence_regs(acc2);
        fence_regs(h[0]);
        fence_regs(h[1]);

        auto layernorm = [&](auto Tc) {
            constexpr int t = decltype(Tc)::value;
            if constexpr (t == SG_LD || t == SG_LD + 1) {
#pragma unroll
                for (int ks = 3 * (t - SG_LD); ks < 3 * (t - SG_LD) + 3; ks++)
                    ldsm4(r[ks][0], r[ks][1], r[ks][2], r[ks][3], ldm_addr + ks * 32);
            }
            if constexpr (t >= SG_S0 && t <= SG_SUM) {
                constexpr int k0 = 2 * (t - SG_S0);
#pragma unroll
                for (int j = 0; j < 2; j++) {
                    const uint32_t v = hadd2(hadd2(r[k0][j], r[k0][j + 2]), hadd2(r[k0 + 1][j], r[k0 + 1][j + 2]));
                    ps[j] = k0 == 0 ? v : hadd2(ps[j], v);
                }
#pragma unroll
                for (int ks = k0; ks < k0 + 2; ks++)
#pragma unroll
                    for (int j = 0; j < 4; j++)
                        sq[j] = ks == 0 ? hmul2(r[ks][j], r[ks][j]) : hfma2(r[ks][j], r[ks][j], sq[j]);
            }
            if constexpr (t == SG_SUM) {
                st[0] = fold(ps[0], ps[1]);
                st[1] = fold(hadd2(sq[0], sq[2]), hadd2(sq[1], sq[3]));
#pragma unroll
                for (int i = 0; i < 2; i++) sx[i] = __shfl_xor_sync(0xffffffffu, st[i], 1);
            }
            if constexpr (t == SG_SH2) {
#pragma unroll
                for (int i = 0; i < 2; i++) {
                    st[i] = hadd2(st[i], sx[i]);
                    sx[i] = __shfl_xor_sync(0xffffffffu, st[i], 2);
                }
            }
            if constexpr (t == SG_RS) {
                const uint32_t s1 = hadd2(st[0], sx[0]), s2 = hadd2(st[1], sx[1]);
                float nm[2], var[2];
                bool poor = false;
#pragma unroll
                for (int j = 0; j < 2; j++) {
                    nm[j] = (j ? bf_hi(s1) : bf_lo(s1)) * (-1.0f / CH);
                    const float m2 = nm[j] * nm[j];
                    var[j] = fmaf(j ? bf_hi(s2) : bf_lo(s2), 1.0f / CH, -m2);
                    poor |= !(4.0f * m2 <= var[j]);
                }
                if (__any_sync(0xffffffffu, poor)) {
                    uint32_t d1[4], d2[4];
#pragma unroll
                    for (int j = 0; j < 4; j++) {
                        const uint32_t c = pack_bf16(nm[j & 1], nm[j & 1]);
#pragma unroll
                        for (int ks = 0; ks < 6; ks++) {
                            r[ks][j] = hadd2(r[ks][j], c);
                            d1[j] = ks == 0 ? r[ks][j] : hadd2(d1[j], r[ks][j]);
                            d2[j] = ks == 0 ? hmul2(r[ks][j], r[ks][j]) : hfma2(r[ks][j], r[ks][j], d2[j]);
                        }
                    }
                    uint32_t v1 = fold(hadd2(d1[0], d1[2]), hadd2(d1[1], d1[3]));
                    uint32_t v2 = fold(hadd2(d2[0], d2[2]), hadd2(d2[1], d2[3]));
#pragma unroll
                    for (int i = 1; i <= 2; i++) {
                        v1 = hadd2(v1, __shfl_xor_sync(0xffffffffu, v1, i));
                        v2 = hadd2(v2, __shfl_xor_sync(0xffffffffu, v2, i));
                    }
#pragma unroll
                    for (int j = 0; j < 2; j++) {
                        nm[j] = (j ? bf_hi(v1) : bf_lo(v1)) * (-1.0f / CH);
                        var[j] = fmaxf(fmaf(j ? bf_hi(v2) : bf_lo(v2), 1.0f / CH, -nm[j] * nm[j]), 0.f);
                    }
                }
#pragma unroll
                for (int j = 0; j < 2; j++) {
                    constexpr float K = 1.0f / (GELU_S * GELU_S);
                    float rs;
                    asm("rsqrt.approx.ftz.f32 %0, %1;" : "=f"(rs) : "f"(fmaf(var[j], K, K * 1e-5f)));
                    rp[j] = pack_bf16(rs, rs);
                    const float c = nm[j] * bf_lo(rp[j]);
                    cp[j] = pack_bf16(c, c);
                }
            }
            if constexpr (t >= SG_CVT && t < SG_CVT + 3) {
#pragma unroll
                for (int ks = 2 * (t - SG_CVT); ks < 2 * (t - SG_CVT) + 2; ks++)
#pragma unroll
                    for (int j = 0; j < 4; j++) a[ks][j] = bf2h(hfma2(r[ks][j], rp[j & 1], cp[j & 1]));
            }
        };
        auto gelu_upto = [&](auto Tc, auto Ec) {
            constexpr int t = decltype(Tc)::value, END = decltype(Ec)::value;
            constexpr int sf = (t + 1) % 24, sb = (t + 23) % 24;
            if constexpr (t >= 0 && t < END) {
#pragma unroll
                for (int i = 0; i < 4; i++) gelu_tanh(tl[t & 1][i], tg[t & 1][i], u[t & 1][i]);
            }
            if constexpr (t + 1 < END) {
#pragma unroll
                for (int i = 0; i < 4; i++) u[(t + 1) & 1][i] = gelu_front(h[(sf / 6) & 1][4 * (sf % 6) + i]);
            }
            if constexpr (t >= 1 && t - 1 < END) {
#pragma unroll
                for (int i = 0; i < 4; i++)
                    p[sb][i] = gelu_back(h[(sb / 6) & 1][4 * (sb % 6) + i], tl[(t + 1) & 1][i], tg[(t + 1) & 1][i]);
            }
        };
        auto gelu = [&](auto Tc) { gelu_upto(Tc, std::integral_constant<int, 99>{}); };
        auto arrive = [&](int bar) {
            __syncwarp();
            mbar_arrive_if(bars + 8 * (bar + wg), lane == 0);
        };
        auto store_out = [&](int i) {
            const int half = i / 3, j = i % 3;
            sts128(out_addr + half * 8 * PXB + j * 64,
                   make_uint4(h2bf(acc2[8 * j + half]), h2bf(acc2[8 * j + 2 + half]), h2bf(acc2[8 * j + 4 + half]),
                              h2bf(acc2[8 * j + 6 + half])));
        };
        auto out_ready = [&](bool pred) {
            asm volatile("fence.proxy.async.shared::cta;" ::: "memory");
            __syncwarp();
            mbar_arrive_if(bars + 8 * (B_OUT_READY + wg), pred && lane == 0);
        };

        mbar_wait(bars + 8 * (B_STG_FULL + 2 * wg), 0);
        TRS_(3);
        static_for<SG_LD, SG_CVT + 3>(layernorm);
        SCHED_FENCE();
        arrive(B_STG_EMPTY);
        WG_FENCE();
#pragma unroll
        for (int ks = 0; ks < 6; ks++) gemm1_step(h[0], a, w1desc, 0, ks);
        WG_COMMIT();
#pragma unroll
        for (int ks = 0; ks < 6; ks++) gemm1_step(h[1], a, w1desc, 1, ks);
        WG_COMMIT();
        wg_wait<1>();
        fence_regs(h[0]);
        static_for<-1, 5>(gelu);
        wg_wait<0>();

        auto segment = [&](auto Tc, auto Lc, int it) {
            constexpr int t = decltype(Tc)::value;
            constexpr bool LAST = decltype(Lc)::value;
            if constexpr (t == 5) {
                wg_wait<0>();
                fence_regs(h[0]);
            } else if constexpr (t % 6 == 5) {
                wg_wait<1>();
            } else if constexpr (t == SG_EPI) {
                wg_wait<2>();
                fence_regs(acc2);
            }
            if constexpr (t % 6 == 5) fence_regs(h[((t + 1) / 6) & 1]);
            if constexpr (t == SG_LD && !LAST) mbar_wait(bars + 8 * (B_STG_FULL + 2 * wg), (it + 1) & 1);
            if constexpr (t == SG_OUT) out_ready(LAST || it > 0);
            if constexpr (t == SG_SUM + 1 && !LAST) arrive(B_STG_EMPTY);
            if constexpr (t == (LAST ? 22 : SG_EPI)) mbar_wait(bars + 8 * (B_OUT_FREE + wg), (it & 1) ^ 1);
            constexpr bool g1seg = t % 6 >= 1 && t % 6 <= 3 && (!LAST || t < 18);
            if constexpr (t <= 25 || g1seg) {
                WG_FENCE();
                if constexpr (t <= 25) {
#pragma unroll
                    for (int j = (t == 5 ? 0 : t - 2); j <= t - 2; j++) gemm2_step(acc2, p[j], w2desc, j);
                }
                if constexpr (g1seg) {
                    if constexpr (t == 25) WG_COMMIT();
                    constexpr int c = (t / 6 + 1) % 4;
                    gemm1_step(h[c & 1], a, w1desc, c, (t % 6 - 1) * 2);
                    gemm1_step(h[c & 1], a, w1desc, c, (t % 6 - 1) * 2 + 1);
                }
                WG_COMMIT();
            }
            gelu_upto(Tc, std::integral_constant<int, (LAST ? 24 : 99)>{});
            if constexpr (t >= SG_EPI) {
#pragma unroll
                for (int i = 3 * (t - SG_EPI); i < 3 * (t - SG_EPI) + 3; i++) store_out(i);
            }
            if constexpr (!LAST) layernorm(Tc);
            SCHED_FENCE();
        };
#pragma unroll 1
        for (int it = 0; it < NT / 2 - 1; it++) {
            static_for<5, 29>([&](auto Tc) { segment(Tc, std::false_type{}, it); });
            wg_wait<0>();
        }
        {
            const uint32_t sb2 = __shfl_sync(0xffffffffu, lds32(bars + 8 * B_BASE), 0);
            w1desc = make_desc(sb2 + SM_W1, W1_LBO, W1_SBO);
            w2desc = make_desc(sb2 + SM_W2, W2_LBO, W2_SBO);
        }
        static_for<5, 26>([&](auto Tc) { segment(Tc, std::true_type{}, NT / 2 - 1); });
        wg_wait<0>();
        fence_regs(acc2);
#pragma unroll
        for (int i = 0; i < 6; i++) store_out(i);
        out_ready(true);
        TRS_(4);
    }
}

typedef CUresult (*PFN_encodeTiled)(CUtensorMap*, CUtensorMapDataType, cuuint32_t, void*, const cuuint64_t*,
                                    const cuuint64_t*, const cuuint32_t*, const cuuint32_t*, CUtensorMapInterleave,
                                    CUtensorMapSwizzle, CUtensorMapL2promotion, CUtensorMapFloatOOBfill);

}

extern "C" void kernel_launch(void* const* d_in, const int* in_sizes, int n_in, void* d_out, int out_size) {
    const __nv_bfloat16* x = (const __nv_bfloat16*)d_in[0];
    const __nv_bfloat16* dwl = (const __nv_bfloat16*)d_in[1];
    const __nv_bfloat16* dws = (const __nv_bfloat16*)d_in[2];
    const __nv_bfloat16* w1 = (const __nv_bfloat16*)d_in[3];
    const __nv_bfloat16* w2 = (const __nv_bfloat16*)d_in[4];

    static PFN_encodeTiled encode = nullptr;
    if (!encode) {
        void* fn = nullptr;
        cudaDriverEntryPointQueryResult qres;
        cudaGetDriverEntryPoint("cuTensorMapEncodeTiled", &fn, cudaEnableDefault, &qres);
        encode = (PFN_encodeTiled)fn;
        cudaFuncSetAttribute(fused_block_kernel, cudaFuncAttributeMaxDynamicSharedMemorySize, SMEM_TOTAL);
    }
    CUtensorMap rowmap, copymap, outmap;
    cuuint64_t gdim[3] = {(cuuint64_t)CH, (cuuint64_t)IMG_W, (cuuint64_t)IMG_H};
    cuuint64_t gstride[2] = {(cuuint64_t)PXB, (cuuint64_t)IMG_W * PXB};
    cuuint32_t estr[4] = {1, 1, 1, 1};
    cuuint32_t box_row[3] = {(cuuint32_t)CH, (cuuint32_t)ROW_PX, 2};
    cuuint32_t box_tile[3] = {(cuuint32_t)CH, (cuuint32_t)BW, (cuuint32_t)TR};
    encode(&rowmap, CU_TENSOR_MAP_DATA_TYPE_BFLOAT16, 3, (void*)x, gdim, gstride, box_row, estr,
           CU_TENSOR_MAP_INTERLEAVE_NONE, CU_TENSOR_MAP_SWIZZLE_NONE, CU_TENSOR_MAP_L2_PROMOTION_L2_256B,
           CU_TENSOR_MAP_FLOAT_OOB_FILL_NONE);
    cuuint64_t cdim[4] = {(cuuint64_t)CH, (cuuint64_t)BW, (cuuint64_t)(IMG_W / BW), (cuuint64_t)IMG_H};
    cuuint64_t cstride[3] = {(cuuint64_t)PXB, (cuuint64_t)BW * PXB, (cuuint64_t)IMG_W * PXB};
    cuuint32_t box_copy[4] = {(cuuint32_t)CH, (cuuint32_t)ROW_PX, 1, 2};
    encode(&copymap, CU_TENSOR_MAP_DATA_TYPE_BFLOAT16, 4, d_out, cdim, cstride, box_copy, estr,
           CU_TENSOR_MAP_INTERLEAVE_NONE, CU_TENSOR_MAP_SWIZZLE_NONE, CU_TENSOR_MAP_L2_PROMOTION_NONE,
           CU_TENSOR_MAP_FLOAT_OOB_FILL_NONE);
    encode(&outmap, CU_TENSOR_MAP_DATA_TYPE_BFLOAT16, 3, d_out, gdim, gstride, box_tile, estr,
           CU_TENSOR_MAP_INTERLEAVE_NONE, CU_TENSOR_MAP_SWIZZLE_NONE, CU_TENSOR_MAP_L2_PROMOTION_NONE,
           CU_TENSOR_MAP_FLOAT_OOB_FILL_NONE);
    fused_block_kernel<<<NCTA, NTHREADS, SMEM_TOTAL>>>(rowmap, copymap, outmap, dwl, dws, w1, w2);
}
```

```cpp
#include <cuda_runtime.h>
#include <cuda_bf16.h>
#include <cuda.h>
#include <stdint.h>
#include <type_traits>

#define TRS_(i)

namespace {

constexpr int IMG_H = 512, IMG_W = 512, CH = 96, HID = 384;
constexpr int BW = 16;
constexpr int TR = 4;
constexpr int NT = 32;
constexpr int NCTA = (IMG_W / BW) * (IMG_H / (TR * NT));
constexpr int PXB = CH * 2;
constexpr int ROW_PX = BW + 4;
constexpr int ROW_BYTES = ROW_PX * PXB;
constexpr int UNIT_BYTES = 2 * ROW_BYTES;
constexpr int NU = 2 * NT + 2;
constexpr int STG_PITCH = 208;
constexpr int STG_BYTES = 64 * STG_PITCH;
constexpr int OUT_BYTES = 64 * PXB;
constexpr int NTHREADS = 512;
constexpr int MLP_REGS = 168, TMA_REGS = 24, CONV_REGS = 512 - 2 * MLP_REGS - TMA_REGS;

constexpr int W1_BYTES = CH * HID * 2;
constexpr int W2_BYTES = HID * CH * 2;
constexpr int WPIECE = 24576;
constexpr int SM_W1 = 0;
constexpr int SM_W2 = SM_W1 + W1_BYTES;
constexpr int SM_RING = SM_W2 + W2_BYTES;
constexpr int SM_OUT = SM_RING + 4 * UNIT_BYTES;
constexpr int SM_STG = SM_OUT + 2 * OUT_BYTES;
constexpr int SM_BAR = SM_STG + 2 * STG_BYTES;
constexpr int SMEM_TOTAL = SM_BAR + 256;
static_assert(SMEM_TOTAL <= 232448, "smem");

constexpr int B_RING_FULL = 0;
constexpr int B_RING_EMPTY = 4;
constexpr int B_STG_FULL = 8;
constexpr int B_STG_EMPTY = 12;
constexpr int B_OUT_READY = 14;
constexpr int B_OUT_FREE = 16;
constexpr int B_COPIED = 18;
constexpr int B_FILTER = 19;
constexpr int B_WEIGHTS = 20;
constexpr int B_BASE = 26;

constexpr int W1_LBO = 8 * HID * 2, W1_SBO = 128;
constexpr int W2_KG = 8 * CH * 2;
constexpr int W2_LBO = 8 * W2_KG, W2_SBO = 128;

constexpr float GELU_S = 0.3292034911525734f;
constexpr uint32_t GELU_CH2 = 0x3FC23FC2u, GELU_CL2 = 0x3B513B51u;
constexpr uint32_t GELU_A2 = 0x40D940D9u;

__device__ __forceinline__ uint32_t smem_u32(const void* p) {
    return (uint32_t)__cvta_generic_to_shared(p);
}
__device__ __forceinline__ uint64_t make_desc(uint32_t addr, uint32_t lbo, uint32_t sbo) {
    return (uint64_t)((addr & 0x3FFFF) >> 4) | ((uint64_t)(lbo >> 4) << 16) | ((uint64_t)(sbo >> 4) << 32);
}
__device__ __forceinline__ void mbar_init(uint32_t bar, uint32_t cnt) {
    asm volatile("mbarrier.init.shared::cta.b64 [%0], %1;" ::"r"(bar), "r"(cnt));
}
__device__ __forceinline__ void mbar_expect_tx(uint32_t bar, uint32_t bytes) {
    asm volatile("mbarrier.arrive.expect_tx.shared::cta.b64 _, [%0], %1;" ::"r"(bar), "r"(bytes) : "memory");
}
__device__ __forceinline__ void mbar_arrive_if(uint32_t bar, bool pred) {
    asm volatile("{\n.reg .pred p;\nsetp.ne.u32 p, %1, 0;\n@p mbarrier.arrive.shared::cta.b64 _, [%0];\n}\n"
                 ::"r"(bar), "r"((uint32_t)pred) : "memory");
}
__device__ __forceinline__ void mbar_wait(uint32_t bar, uint32_t parity) {
    asm volatile(
        "{\n"
        ".reg .pred p;\n"
        "WAIT_LOOP:\n"
        "mbarrier.try_wait.parity.shared::cta.b64 p, [%0], %1, %2;\n"
        "@p bra WAIT_DONE;\n"
        "bra WAIT_LOOP;\n"
        "WAIT_DONE:\n"
        "}\n" ::"r"(bar), "r"(parity), "r"(20000) : "memory");
}
__device__ __forceinline__ void tma_load3d(uint32_t dst, const CUtensorMap* map, int cx, int cy, uint32_t bar) {
    asm volatile(
        "cp.async.bulk.tensor.3d.shared::cluster.global.mbarrier::complete_tx::bytes [%0], [%1, {%2, %3, %4}], [%5];"
        ::"r"(dst), "l"((uint64_t)map), "r"(0), "r"(cx), "r"(cy), "r"(bar) : "memory");
}
__device__ __forceinline__ void bulk_load(uint32_t dst, const void* src, uint32_t bytes, uint32_t bar) {
    asm volatile("cp.async.bulk.shared::cluster.global.mbarrier::complete_tx::bytes [%0], [%1], %2, [%3];"
                 ::"r"(dst), "l"(src), "r"(bytes), "r"(bar) : "memory");
}
__device__ __forceinline__ uint4 lds128(uint32_t addr) {
    uint4 v;
    asm volatile("ld.shared.v4.u32 {%0,%1,%2,%3}, [%4];" : "=r"(v.x), "=r"(v.y), "=r"(v.z), "=r"(v.w) : "r"(addr));
    return v;
}
__device__ __forceinline__ uint32_t lds32(uint32_t addr) {
    uint32_t v;
    asm volatile("ld.shared.u32 %0, [%1];" : "=r"(v) : "r"(addr));
    return v;
}
__device__ __forceinline__ void sts128(uint32_t addr, uint4 v) {
    asm volatile("st.shared.v4.u32 [%0], {%1,%2,%3,%4};" ::"r"(addr), "r"(v.x), "r"(v.y), "r"(v.z), "r"(v.w) : "memory");
}
__device__ __forceinline__ void sts32(uint32_t addr, uint32_t a) {
    asm volatile("st.shared.u32 [%0], %1;" ::"r"(addr), "r"(a) : "memory");
}
__device__ __forceinline__ void ldsm4(uint32_t& a, uint32_t& b, uint32_t& c, uint32_t& d, uint32_t addr) {
    asm volatile("ldmatrix.sync.aligned.m8n8.x4.shared.b16 {%0,%1,%2,%3}, [%4];"
                 : "=r"(a), "=r"(b), "=r"(c), "=r"(d) : "r"(addr));
}
__device__ __forceinline__ void ldsm2(uint32_t& a, uint32_t& b, uint32_t addr) {
    asm volatile("ldmatrix.sync.aligned.m8n8.x2.shared.b16 {%0,%1}, [%2];" : "=r"(a), "=r"(b) : "r"(addr));
}
__device__ __forceinline__ void stsm4(uint32_t addr, uint32_t a, uint32_t b, uint32_t c, uint32_t d) {
    asm volatile("stmatrix.sync.aligned.m8n8.x4.shared.b16 [%0], {%1,%2,%3,%4};"
                 ::"r"(addr), "r"(a), "r"(b), "r"(c), "r"(d) : "memory");
}
__device__ __forceinline__ void stsm2(uint32_t addr, uint32_t a, uint32_t b) {
    asm volatile("stmatrix.sync.aligned.m8n8.x2.shared.b16 [%0], {%1,%2};" ::"r"(addr), "r"(a), "r"(b) : "memory");
}
__device__ __forceinline__ uint32_t hfma2(uint32_t a, uint32_t b, uint32_t c) {
    uint32_t d;
    asm("fma.rn.bf16x2 %0, %1, %2, %3;" : "=r"(d) : "r"(a), "r"(b), "r"(c));
    return d;
}
__device__ __forceinline__ uint32_t hmul2(uint32_t a, uint32_t b) {
    uint32_t d;
    asm("mul.rn.bf16x2 %0, %1, %2;" : "=r"(d) : "r"(a), "r"(b));
    return d;
}
__device__ __forceinline__ uint32_t hadd2(uint32_t a, uint32_t b) {
    uint32_t d;
    asm("add.rn.bf16x2 %0, %1, %2;" : "=r"(d) : "r"(a), "r"(b));
    return d;
}
__device__ __forceinline__ uint32_t hsub2(uint32_t a, uint32_t b) {
    uint32_t d;
    asm("sub.rn.bf16x2 %0, %1, %2;" : "=r"(d) : "r"(a), "r"(b));
    return d;
}
__device__ __forceinline__ uint32_t fold(uint32_t a, uint32_t b) {
    return hadd2(__byte_perm(a, b, 0x5410), __byte_perm(a, b, 0x7632));
}
__device__ __forceinline__ float bf_lo(uint32_t v) { return __uint_as_float(v << 16); }
__device__ __forceinline__ float bf_hi(uint32_t v) { return __uint_as_float(v & 0xffff0000u); }
__device__ __forceinline__ uint32_t pack_bf16(float lo, float hi) {
    uint32_t d;
    asm("cvt.rn.bf16x2.f32 %0, %1, %2;" : "=r"(d) : "f"(hi), "f"(lo));
    return d;
}
__device__ __forceinline__ uint32_t pack_f16(float lo, float hi) {
    uint32_t d;
    asm("cvt.rn.f16x2.f32 %0, %1, %2;" : "=r"(d) : "f"(hi), "f"(lo));
    return d;
}
__device__ __forceinline__ uint32_t bf2h(uint32_t v) { return pack_f16(bf_lo(v), bf_hi(v)); }
__device__ __forceinline__ uint4 bf2h4(uint4 v) { return make_uint4(bf2h(v.x), bf2h(v.y), bf2h(v.z), bf2h(v.w)); }
__device__ __forceinline__ uint32_t mulc(uint32_t v) { return hfma2(v, GELU_CH2, hmul2(v, GELU_CL2)); }
__device__ __forceinline__ uint32_t h2bf(uint32_t h) {
    float lo, hi;
    asm("{\n.reg .b16 l, h;\nmov.b32 {l, h}, %2;\ncvt.f32.f16 %0, l;\ncvt.f32.f16 %1, h;\n}\n" : "=f"(lo), "=f"(hi) : "r"(h));
    return pack_bf16(lo, hi);
}

#define WG_FENCE() asm volatile("wgmma.fence.sync.aligned;" ::: "memory")
#define WG_COMMIT() asm volatile("wgmma.commit_group.sync.aligned;" ::: "memory")
template <int N>
__device__ __forceinline__ void wg_wait() {
    asm volatile("wgmma.wait_group.sync.aligned %0;" ::"n"(N) : "memory");
}
#define SCHED_FENCE() asm volatile("pmevent.mask 0;" ::: "memory")

template <bool ACC>
__device__ __forceinline__ void wgmma_rs(uint32_t (&d)[24], const uint32_t (&a)[4], uint64_t desc) {
    asm volatile(
        "{\n"
        ".reg .pred p;\n"
        "setp.ne.b32 p, %29, 0;\n"
        "wgmma.mma_async.sync.aligned.m64n96k16.f16.f16.f16 {"
        "%0,%1,%2,%3,%4,%5,%6,%7,%8,%9,%10,%11,%12,%13,%14,%15,"
        "%16,%17,%18,%19,%20,%21,%22,%23"
        "}, {%24,%25,%26,%27}, %28, p, 1, 1, 1;\n"
        "}\n"
        : "+r"(d[0]), "+r"(d[1]), "+r"(d[2]), "+r"(d[3]), "+r"(d[4]), "+r"(d[5]), "+r"(d[6]), "+r"(d[7]),
          "+r"(d[8]), "+r"(d[9]), "+r"(d[10]), "+r"(d[11]), "+r"(d[12]), "+r"(d[13]), "+r"(d[14]), "+r"(d[15]),
          "+r"(d[16]), "+r"(d[17]), "+r"(d[18]), "+r"(d[19]), "+r"(d[20]), "+r"(d[21]), "+r"(d[22]), "+r"(d[23])
        : "r"(a[0]), "r"(a[1]), "r"(a[2]), "r"(a[3]), "l"(desc), "n"(ACC ? 1 : 0));
}
__device__ __forceinline__ void gemm1_step(uint32_t (&h)[24], const uint32_t (&a)[6][4], uint64_t w1desc, int c, int ks) {
    const uint64_t d = w1desc + (uint64_t)((c * 12 * W1_SBO + ks * 2 * W1_LBO) >> 4);
    if (ks == 0) wgmma_rs<false>(h, a[0], d);
    else wgmma_rs<true>(h, a[ks], d);
}
__device__ __forceinline__ void gemm2_step(uint32_t (&acc2)[24], const uint32_t (&p)[4], uint64_t w2desc, int j) {
    const uint64_t d = w2desc + (uint64_t)(((16 * (j % 3) + j / 3) * W2_KG) >> 4);
    if (j == 0) wgmma_rs<false>(acc2, p, d);
    else wgmma_rs<true>(acc2, p, d);
}
__device__ __forceinline__ uint32_t gelu_front(uint32_t y) {
    uint32_t t, u;
    asm("fma.rn.f16x2 %0, %1, %1, %2;" : "=r"(t) : "r"(y), "r"(GELU_A2));
    asm("mul.rn.f16x2 %0, %1, %2;" : "=r"(u) : "r"(y), "r"(t));
    return u;
}
__device__ __forceinline__ void gelu_tanh(uint16_t& lo, uint16_t& hi, uint32_t u) {
    asm("{\n.reg .b16 l, h;\nmov.b32 {l, h}, %2;\ntanh.approx.f16 %0, l;\ntanh.approx.f16 %1, h;\n}\n"
        : "=h"(lo), "=h"(hi) : "r"(u));
}
__device__ __forceinline__ uint32_t gelu_back(uint32_t y, uint16_t lo, uint16_t hi) {
    uint32_t g;
    asm("{\n.reg .b32 t;\nmov.b32 t, {%2, %3};\nfma.rn.f16x2 %0, %1, t, %1;\n}\n" : "=r"(g) : "r"(y), "h"(lo), "h"(hi));
    return g;
}

template <int B, int E, typename F>
__device__ __forceinline__ void static_for(F&& f) {
    if constexpr (B < E) {
        f(std::integral_constant<int, B>{});
        static_for<B + 1, E>(f);
    }
}

template <int NP, int R0, int R1 = 5>
__device__ __forceinline__ void conv_row(uint32_t (&o)[2 * NP], uint32_t (&acc)[4][NP][3], const uint32_t (&w)[5][7],
                                         const uint32_t (&x)[2 * NP + 4]) {
    uint32_t e[NP + 1], f[NP + 1], t[5][NP][3];
#pragma unroll
    for (int i = 0; i <= NP; i++) {
        e[i] = hsub2(x[2 * i], x[2 * i + 1]);
        f[i] = hsub2(x[2 * i + 2], x[2 * i + 1]);
    }
#pragma unroll
    for (int p = 0; p < NP; p++) {
#pragma unroll
        for (int r = R0; r < R1; r++) {
            const uint32_t(&h)[7] = w[4 - r];
            t[r][p][1] = r < 4 ? hfma2(x[2 * p + 1], h[3], acc[r & 3][p][1]) : hmul2(x[2 * p + 1], h[3]);
            t[r][p][0] = r < 4 ? hfma2(x[2 * p + 4], h[2], acc[r & 3][p][0]) : hmul2(x[2 * p + 4], h[2]);
            t[r][p][2] = r < 4 ? hfma2(x[2 * p + 5], h[2], acc[r & 3][p][2]) : hmul2(x[2 * p + 5], h[2]);
        }
#pragma unroll
        for (int r = R0; r < R1; r++) {
            const uint32_t(&h)[7] = w[4 - r];
            t[r][p][1] = hfma2(x[2 * p + 3], h[4], t[r][p][1]);
            t[r][p][0] = hfma2(e[p], h[0], t[r][p][0]);
            t[r][p][2] = hfma2(f[p], h[5], t[r][p][2]);
        }
#pragma unroll
        for (int r = R0; r < R1; r++) {
            const uint32_t(&h)[7] = w[4 - r];
            t[r][p][0] = hfma2(e[p + 1], h[1], t[r][p][0]);
            t[r][p][2] = hfma2(f[p + 1], h[6], t[r][p][2]);
        }
        if (R0 == 0) {
            o[2 * p] = hadd2(t[0][p][0], t[0][p][1]);
            o[2 * p + 1] = hadd2(t[0][p][1], t[0][p][2]);
        }
#pragma unroll
        for (int r = (R0 > 0 ? R0 : 1); r < R1; r++)
#pragma unroll
            for (int m = 0; m < 3; m++) acc[r - 1][p][m] = t[r][p][m];
    }
}

constexpr int SG_LD = 11, SG_S0 = 12, SG_SUM = 14, SG_SH2 = 15, SG_RS = 16, SG_CVT = 18;
constexpr int SG_OUT = 6;
constexpr int SG_EPI = 27;

__global__ void __launch_bounds__(NTHREADS, 1)
fused_block_kernel(const __grid_constant__ CUtensorMap rowmap, const __grid_constant__ CUtensorMap copymap,
                   const __grid_constant__ CUtensorMap outmap,
                   const __nv_bfloat16* __restrict__ dwl, const __nv_bfloat16* __restrict__ dws,
                   const __nv_bfloat16* __restrict__ w1, const __nv_bfloat16* __restrict__ w2) {
    extern __shared__ __align__(1024) uint8_t smem[];
    const uint32_t sbase = smem_u32(smem);
    const int tid = threadIdx.x;
    const int wid = __shfl_sync(0xffffffffu, tid >> 5, 0) ^ 8;
    const int wg = wid >> 2, warp = wid & 3;
    const int lane = tid & 31;
    const uint32_t bars = sbase + SM_BAR;
    const int x0 = (blockIdx.x >> 2) * BW, y0 = (blockIdx.x & 3) * (TR * NT);

    if (tid == NTHREADS - 128) {
        const char* w1b = reinterpret_cast<const char*>(w1);
        const char* w2b = reinterpret_cast<const char*>(w2);
        asm volatile("cp.async.bulk.prefetch.L2.global [%0], %1;"
                     ::"l"(((blockIdx.x & 1) ? w2b : w1b) + (blockIdx.x >> 1) * (W1_BYTES / (NCTA / 2))), "r"(W1_BYTES / (NCTA / 2))
                     : "memory");
        mbar_init(bars + 8 * B_FILTER, 1);
#pragma unroll
        for (int i = 0; i < 4; i++) mbar_init(bars + 8 * (B_RING_FULL + i), 1);
#pragma unroll
        for (int i = 0; i < 6; i++) mbar_init(bars + 8 * (B_WEIGHTS + i), 1);
        asm volatile("fence.mbarrier_init.release.cluster;" ::: "memory");
        mbar_expect_tx(bars + 8 * B_FILTER, 34 * PXB);
        bulk_load(sbase + SM_OUT, dws, 25 * PXB, bars + 8 * B_FILTER);
        bulk_load(sbase + SM_OUT + 25 * PXB, dwl, 9 * PXB, bars + 8 * B_FILTER);
#pragma unroll
        for (int i = 0; i < 6; i++) {
            if (i < 2) {
#pragma unroll
                for (int u = 2 * i; u < 2 * i + 2; u++) {
                    mbar_expect_tx(bars + 8 * (B_RING_FULL + u), UNIT_BYTES);
                    tma_load3d(sbase + SM_RING + u * UNIT_BYTES, &rowmap, x0 - 2, y0 - 2 + 2 * u, bars + 8 * (B_RING_FULL + u));
                }
            }
            mbar_expect_tx(bars + 8 * (B_WEIGHTS + i), WPIECE);
            bulk_load(sbase + i * WPIECE, (i < 3 ? w1b : w2b) + (i % 3) * WPIECE, WPIECE, bars + 8 * (B_WEIGHTS + i));
        }
    } else if (tid == NTHREADS - 96) {
#pragma unroll
        for (int m = 0; m < 2; m++) {
            mbar_init(bars + 8 * (B_RING_EMPTY + 2 * m), 4);
            mbar_init(bars + 8 * (B_RING_EMPTY + 2 * m + 1), 4);
            mbar_init(bars + 8 * (B_STG_FULL + 2 * m), 4);
            mbar_init(bars + 8 * (B_STG_EMPTY + m), 4);
            mbar_init(bars + 8 * (B_OUT_READY + m), 4);
            mbar_init(bars + 8 * (B_OUT_FREE + m), 1);
        }
        mbar_init(bars + 8 * B_COPIED, 2);
        sts32(bars + 8 * B_BASE, sbase);
        asm volatile("fence.mbarrier_init.release.cluster;" ::: "memory");
    }
    __syncthreads();

    if (wg == 3) {
        asm volatile("setmaxnreg.dec.sync.aligned.u32 %0;" ::"n"(TMA_REGS));
        const int m = warp >> 1;
        if (lane == 0) {
            if (warp == 0 || warp == 3) {
#pragma unroll 1
                for (int u = 2 * m; u < NU - 1; u += (u & 1) ? 3 : 1) {
                    const uint32_t fb = bars + 8 * (B_RING_FULL + (u & 3)), buf = sbase + SM_RING + (u & 3) * UNIT_BYTES;
                    mbar_wait(bars + 8 * (B_RING_EMPTY + (u & 3)), (u >> 2) & 1);
                    if (u != 0) {
                        asm volatile("cp.async.bulk.tensor.4d.global.shared::cta.bulk_group [%0, {%1, %2, %3, %4}], [%5];"
                                     ::"l"((uint64_t)&copymap), "r"(0), "r"(0), "r"(blockIdx.x >> 2), "r"(y0 - 2 + 2 * u),
                                     "r"(buf + 2 * PXB) : "memory");
                        asm volatile("cp.async.bulk.commit_group;" ::: "memory");
                        asm volatile("cp.async.bulk.wait_group 0;" ::: "memory");
                    }
                    if (u + 4 < NU) {
                        mbar_expect_tx(fb, UNIT_BYTES);
                        tma_load3d(buf, &rowmap, x0 - 2, y0 + 6 + 2 * u, fb);
                    }
                }
                mbar_arrive_if(bars + 8 * B_COPIED, true);
            } else {
                const uint32_t buf = sbase + SM_OUT + m * OUT_BYTES;
#pragma unroll 1
                for (int i = 0; i < NT / 2; i++) {
                    if (i == NT / 2 - 1) mbar_wait(bars + 8 * B_COPIED, 0);
                    mbar_wait(bars + 8 * (B_OUT_READY + m), i & 1);
                    asm volatile("cp.reduce.async.bulk.tensor.3d.global.shared::cta.add.bulk_group [%0, {%1, %2, %3}], [%4];"
                                 ::"l"((uint64_t)&outmap), "r"(0), "r"(x0), "r"(y0 + TR * (2 * i + m)), "r"(buf) : "memory");
                    asm volatile("cp.async.bulk.commit_group;" ::: "memory");
                    asm volatile("cp.async.bulk.wait_group 0;" ::: "memory");
                    mbar_arrive_if(bars + 8 * (B_OUT_FREE + m), true);
                }
            }
        }
    } else if (wg == 2) {
        asm volatile("setmaxnreg.inc.sync.aligned.u32 %0;" ::"n"(CONV_REGS));
        uint32_t wa[5][7], wb[5][7];
        {
            const uint32_t pa = sbase + SM_OUT + 4 * lane, pb = sbase + SM_OUT + 4 * (32 + (lane & 15));
            const bool mir = lane >= 16;
            mbar_wait(bars + 8 * B_FILTER, 0);
#pragma unroll
            for (int r = 0; r < 5; r++) {
                uint32_t u[5], v[5];
#pragma unroll
                for (int c = 0; c < 5; c++) {
                    u[c] = lds32(pa + (5 * r + c) * PXB);
                    v[c] = lds32(pb + (5 * r + c) * PXB);
                    if (r >= 1 && r <= 3 && c >= 1 && c <= 3) {
                        u[c] = hadd2(u[c], lds32(pa + (25 + 3 * (r - 1) + c - 1) * PXB));
                        v[c] = hadd2(v[c], lds32(pb + (25 + 3 * (r - 1) + c - 1) * PXB));
                    }
                }
#pragma unroll
                for (int c = 0; c < 2; c++) {
                    const uint32_t lo = v[c], hi = v[4 - c];
                    v[c] = mir ? hi : lo;
                    v[4 - c] = mir ? lo : hi;
                }
                wa[r][0] = u[0]; wa[r][1] = u[2]; wa[r][2] = u[4]; wa[r][3] = hadd2(u[0], u[1]);
                wa[r][4] = hadd2(u[2], u[3]); wa[r][5] = u[1]; wa[r][6] = u[3];
                wb[r][0] = v[0]; wb[r][1] = v[2]; wb[r][2] = v[4]; wb[r][3] = hadd2(v[0], v[1]);
                wb[r][4] = hadd2(v[2], v[3]); wb[r][5] = v[1]; wb[r][6] = v[3];
            }
        }
        const int mi = lane >> 3, mr = lane & 7, up = mr >> 2;
        const uint32_t ring_a = sbase + SM_RING + (4 * warp + mi) * PXB + mr * 16;
        const uint32_t ring_b0 = sbase + SM_RING + (4 * warp + (up ? 7 - mi : mi)) * PXB + 128 + (mr & 3) * 16;
        const uint32_t ring_b1 = sbase + SM_RING + (4 * warp + (up ? 3 - mi : 4 + mi)) * PXB + 128 + (mr & 3) * 16;
        const uint32_t stg_a = sbase + SM_STG + (4 * warp + mi) * STG_PITCH + mr * 16;
        const uint32_t stg_b = sbase + SM_STG + (4 * warp + (up ? 3 - mi : mi)) * STG_PITCH + 128 + (mr & 3) * 16;
        uint32_t acca[4][2][3], accb[4][1][3], xa[8], xb[6], oa[4], ob[2];
        auto fetch_a = [&](uint32_t off) {
            ldsm4(xa[0], xa[1], xa[2], xa[3], ring_a + off);
            ldsm4(xa[4], xa[5], xa[6], xa[7], ring_a + off + 4 * PXB);
        };
        auto fetch_b = [&](uint32_t off) {
            ldsm4(xb[0], xb[1], xb[2], xb[3], ring_b0 + off);
            ldsm2(xb[4], xb[5], ring_b1 + off);
        };
        const uint32_t arr = bars + 8 * (lane == 0 ? B_RING_EMPTY + 3 : B_STG_FULL);
        TRS_(0);
        static_for<0, 4>([&](auto Rc) {
            constexpr int R = decltype(Rc)::value;
            if (R % 2 == 0) mbar_wait(bars + 8 * (B_RING_FULL + R / 2), 0);
            fetch_a(R * ROW_BYTES);
            fetch_b(R * ROW_BYTES);
            conv_row<2, 4 - R>(oa, acca, wa, xa);
            conv_row<1, 4 - R>(ob, accb, wb, xb);
        });
        SCHED_FENCE();
        __syncwarp();
        mbar_arrive_if(bars + 8 * (B_RING_EMPTY + lane), lane < 2);
        mbar_wait(bars + 8 * (B_RING_FULL + 2), 0);
        fetch_a(4 * ROW_BYTES);
        fetch_b(4 * ROW_BYTES);
        TRS_(5);
        auto tile = [&](auto Sc, auto Lc, uint32_t ph) {
            constexpr int s = decltype(Sc)::value;
            constexpr bool LAST = decltype(Lc)::value;
            static_for<0, 4>([&](auto Rc) {
                constexpr int R = decltype(Rc)::value, R1 = LAST ? 4 - R : 5;
                constexpr int nrow = (4 * (s ^ 1) + R + 1) & 7;
                constexpr bool more = !LAST || R < 3;
                constexpr uint32_t dst = s * STG_BYTES + R * (BW * STG_PITCH);
                conv_row<2, 0, R1>(oa, acca, wa, xa);
                if (R == 0) mbar_wait(bars + 8 * (B_STG_EMPTY + s), ph ^ 1);
                if ((R & 1) && more) mbar_wait(bars + 8 * (B_RING_FULL + nrow / 2), (s == 0 && R == 1) ? ph : ph ^ 1);
                if (more) fetch_a(nrow * ROW_BYTES);
                stsm4(stg_a + dst, oa[0], oa[1], oa[2], oa[3]);
                conv_row<1, 0, R1>(ob, accb, wb, xb);
                if (more) fetch_b(nrow * ROW_BYTES);
                stsm2(stg_b + dst, ob[0], ob[1]);
                if (R & 1) __syncwarp();
                if (R == 1) mbar_arrive_if(bars + 8 * (B_RING_EMPTY + 2 * (s ^ 1)), lane == 0);
                if (R == 3) mbar_arrive_if(arr ^ (16 * s), lane < 2);
                if (R < 3 || s == 0) SCHED_FENCE();
            });
        };
#pragma unroll 1
        for (int k = 0; k < NT / 2 - 1; k++) {
            tile(std::integral_constant<int, 0>{}, std::false_type{}, k & 1);
            tile(std::integral_constant<int, 1>{}, std::false_type{}, k & 1);
        }
        SCHED_FENCE();
        tile(std::integral_constant<int, 0>{}, std::false_type{}, (NT / 2 - 1) & 1);
        tile(std::integral_constant<int, 1>{}, std::true_type{}, (NT / 2 - 1) & 1);
        TRS_(4);
    } else {
        asm volatile("setmaxnreg.inc.sync.aligned.u32 %0;" ::"n"(MLP_REGS));
        TRS_(0);
        {
            const int kk = lane & 7, a0 = (kk + (lane >> 3)) & 7;
#pragma unroll 1
            for (int t = wid; t < 24; t += 8) {
                const uint32_t base = sbase + SM_W1 + (t >> 1) * W1_LBO + (t & 1) * 384;
                uint4 v[6];
                mbar_wait(bars + 8 * (B_WEIGHTS + (t >> 3)), 0);
#pragma unroll
                for (int i = 0; i < 6; i++) v[i] = lds128(base + (i >> 1) * 128 + kk * (HID * 2) + (a0 ^ ((i & 1) * 4)) * 16);
                __syncwarp();
#pragma unroll
                for (int i = 0; i < 6; i++)
                    sts128(base + (i >> 1) * 128 + (a0 ^ ((i & 1) * 4)) * (HID * 2) + kk * 16, bf2h4(v[i]));
            }
            asm volatile("fence.proxy.async.shared::cta;" ::: "memory");
            asm volatile("bar.sync 1, 256;" ::: "memory");
            TRS_(1);
            const uint32_t src = sbase + SM_W2 + (lane >> 2) * (CH * 2) + (lane & 3) * 16, dst = sbase + SM_W2 + lane * 16;
#pragma unroll 1
            for (int t = wg ? 16 + warp : warp; t < (wg ? 48 : 16); t += 4) {
                uint4 v[3];
                mbar_wait(bars + 8 * (B_WEIGHTS + 3 + (t >> 4)), 0);
#pragma unroll
                for (int i = 0; i < 3; i++) v[i] = lds128(src + t * W2_KG + i * 64);
                __syncwarp();
#pragma unroll
                for (int i = 0; i < 3; i++) {
                    const uint4 c = bf2h4(make_uint4(mulc(v[i].x), mulc(v[i].y), mulc(v[i].z), mulc(v[i].w)));
                    stsm4(dst + t * W2_KG + i * 512, c.x, c.y, c.z, c.w);
                }
            }
            asm volatile("fence.proxy.async.shared::cta;" ::: "memory");
            asm volatile("bar.arrive %0, 256;" ::"r"(2 + wg) : "memory");
            TRS_(2);
        }

        uint64_t w1desc = make_desc(sbase + SM_W1, W1_LBO, W1_SBO);
        uint64_t w2desc = make_desc(sbase + SM_W2, W2_LBO, W2_SBO);
        const uint32_t ldm_addr = sbase + SM_STG + wg * STG_BYTES +
                                  (16 * warp + (lane & 7) + ((lane >> 3) & 1) * 8) * STG_PITCH + (lane >> 4) * 16;
        const uint32_t out_addr = sbase + SM_OUT + wg * OUT_BYTES + (16 * warp + (lane >> 2)) * PXB + (lane & 3) * 16;

        uint32_t a[6][4], r[6][4];
        uint32_t h[2][24], acc2[24];
        uint32_t p[24][4], u[2][4];
        uint16_t tl[2][4], tg[2][4];
        uint32_t ps[2], sq[4], rp[2], cp[2], st[2], sx[2];
        auto fence_regs = [&](auto& v) {
#pragma unroll
            for (int i = 0; i < (int)(sizeof(v) / 4); i++) asm volatile("" : "+r"(v[i]) :: "memory");
        };
#pragma unroll
        for (int i = 0; i < 24; i++) acc2[i] = h[0][i] = h[1][i] = 0u;
        fence_regs(acc2);
        fence_regs(h[0]);
        fence_regs(h[1]);

        auto layernorm = [&](auto Tc) {
            constexpr int t = decltype(Tc)::value;
            if constexpr (t == SG_LD || t == SG_LD + 1) {
#pragma unroll
                for (int ks = 3 * (t - SG_LD); ks < 3 * (t - SG_LD) + 3; ks++)
                    ldsm4(r[ks][0], r[ks][1], r[ks][2], r[ks][3], ldm_addr + ks * 32);
            }
            if constexpr (t >= SG_S0 && t <= SG_SUM) {
                constexpr int k0 = 2 * (t - SG_S0);
#pragma unroll
                for (int j = 0; j < 2; j++) {
                    const uint32_t v = hadd2(hadd2(r[k0][j], r[k0][j + 2]), hadd2(r[k0 + 1][j], r[k0 + 1][j + 2]));
                    ps[j] = k0 == 0 ? v : hadd2(ps[j], v);
                }
#pragma unroll
                for (int ks = k0; ks < k0 + 2; ks++)
#pragma unroll
                    for (int j = 0; j < 4; j++)
                        sq[j] = ks == 0 ? hmul2(r[ks][j], r[ks][j]) : hfma2(r[ks][j], r[ks][j], sq[j]);
            }
            if constexpr (t == SG_SUM) {
                st[0] = fold(ps[0], ps[1]);
                st[1] = fold(hadd2(sq[0], sq[2]), hadd2(sq[1], sq[3]));
#pragma unroll
                for (int i = 0; i < 2; i++) sx[i] = __shfl_xor_sync(0xffffffffu, st[i], 1);
            }
            if constexpr (t == SG_SH2) {
#pragma unroll
                for (int i = 0; i < 2; i++) {
                    st[i] = hadd2(st[i], sx[i]);
                    sx[i] = __shfl_xor_sync(0xffffffffu, st[i], 2);
                }
            }
            if constexpr (t == SG_RS) {
                const uint32_t s1 = hadd2(st[0], sx[0]), s2 = hadd2(st[1], sx[1]);
                float nm[2], var[2];
                bool poor = false;
#pragma unroll
                for (int j = 0; j < 2; j++) {
                    nm[j] = (j ? bf_hi(s1) : bf_lo(s1)) * (-1.0f / CH);
                    const float m2 = nm[j] * nm[j];
                    var[j] = fmaf(j ? bf_hi(s2) : bf_lo(s2), 1.0f / CH, -m2);
                    poor |= !(4.0f * m2 <= var[j]);
                }
                if (__any_sync(0xffffffffu, poor)) {
                    uint32_t d1[4], d2[4];
#pragma unroll
                    for (int j = 0; j < 4; j++) {
                        const uint32_t c = pack_bf16(nm[j & 1], nm[j & 1]);
#pragma unroll
                        for (int ks = 0; ks < 6; ks++) {
                            r[ks][j] = hadd2(r[ks][j], c);
                            d1[j] = ks == 0 ? r[ks][j] : hadd2(d1[j], r[ks][j]);
                            d2[j] = ks == 0 ? hmul2(r[ks][j], r[ks][j]) : hfma2(r[ks][j], r[ks][j], d2[j]);
                        }
                    }
                    uint32_t v1 = fold(hadd2(d1[0], d1[2]), hadd2(d1[1], d1[3]));
                    uint32_t v2 = fold(hadd2(d2[0], d2[2]), hadd2(d2[1], d2[3]));
#pragma unroll
                    for (int i = 1; i <= 2; i++) {
                        v1 = hadd2(v1, __shfl_xor_sync(0xffffffffu, v1, i));
                        v2 = hadd2(v2, __shfl_xor_sync(0xffffffffu, v2, i));
                    }
#pragma unroll
                    for (int j = 0; j < 2; j++) {
                        nm[j] = (j ? bf_hi(v1) : bf_lo(v1)) * (-1.0f / CH);
                        var[j] = fmaxf(fmaf(j ? bf_hi(v2) : bf_lo(v2), 1.0f / CH, -nm[j] * nm[j]), 0.f);
                    }
                }
#pragma unroll
                for (int j = 0; j < 2; j++) {
                    constexpr float K = 1.0f / (GELU_S * GELU_S);
                    float rs;
                    asm("rsqrt.approx.ftz.f32 %0, %1;" : "=f"(rs) : "f"(fmaf(var[j], K, K * 1e-5f)));
                    rp[j] = pack_bf16(rs, rs);
                    const float c = nm[j] * bf_lo(rp[j]);
                    cp[j] = pack_bf16(c, c);
                }
            }
            if constexpr (t >= SG_CVT && t < SG_CVT + 3) {
#pragma unroll
                for (int ks = 2 * (t - SG_CVT); ks < 2 * (t - SG_CVT) + 2; ks++)
#pragma unroll
                    for (int j = 0; j < 4; j++) a[ks][j] = bf2h(hfma2(r[ks][j], rp[j & 1], cp[j & 1]));
            }
        };
        auto gelu_upto = [&](auto Tc, auto Ec) {
            constexpr int t = decltype(Tc)::value, END = decltype(Ec)::value;
            constexpr int sf = (t + 1) % 24, sb = (t + 23) % 24;
            if constexpr (t >= 0 && t < END) {
#pragma unroll
                for (int i = 0; i < 4; i++) gelu_tanh(tl[t & 1][i], tg[t & 1][i], u[t & 1][i]);
            }
            if constexpr (t + 1 < END) {
#pragma unroll
                for (int i = 0; i < 4; i++) u[(t + 1) & 1][i] = gelu_front(h[(sf / 6) & 1][4 * (sf % 6) + i]);
            }
            if constexpr (t >= 1 && t - 1 < END) {
#pragma unroll
                for (int i = 0; i < 4; i++)
                    p[sb][i] = gelu_back(h[(sb / 6) & 1][4 * (sb % 6) + i], tl[(t + 1) & 1][i], tg[(t + 1) & 1][i]);
            }
        };
        auto gelu = [&](auto Tc) { gelu_upto(Tc, std::integral_constant<int, 99>{}); };
        auto arrive = [&](int bar) {
            __syncwarp();
            mbar_arrive_if(bars + 8 * (bar + wg), lane == 0);
        };
        auto store_out = [&](int i) {
            const int half = i / 3, j = i % 3;
            sts128(out_addr + half * 8 * PXB + j * 64,
                   make_uint4(h2bf(acc2[8 * j + half]), h2bf(acc2[8 * j + 2 + half]), h2bf(acc2[8 * j + 4 + half]),
                              h2bf(acc2[8 * j + 6 + half])));
        };
        auto out_ready = [&](bool pred) {
            asm volatile("fence.proxy.async.shared::cta;" ::: "memory");
            __syncwarp();
            mbar_arrive_if(bars + 8 * (B_OUT_READY + wg), pred && lane == 0);
        };

        mbar_wait(bars + 8 * (B_STG_FULL + 2 * wg), 0);
        TRS_(3);
        static_for<SG_LD, SG_CVT + 3>(layernorm);
        SCHED_FENCE();
        arrive(B_STG_EMPTY);
        WG_FENCE();
#pragma unroll
        for (int ks = 0; ks < 6; ks++) gemm1_step(h[0], a, w1desc, 0, ks);
        WG_COMMIT();
#pragma unroll
        for (int ks = 0; ks < 6; ks++) gemm1_step(h[1], a, w1desc, 1, ks);
        WG_COMMIT();
        wg_wait<1>();
        fence_regs(h[0]);
        static_for<-1, 5>(gelu);
        wg_wait<0>();
        asm volatile("bar.sync %0, 256;" ::"r"(3 - wg) : "memory");
        asm volatile("bar.sync %0, 128;" ::"r"(4 + wg) : "memory");

        auto segment = [&](auto Tc, auto Lc, int it) {
            constexpr int t = decltype(Tc)::value;
            constexpr bool LAST = decltype(Lc)::value;
            if constexpr (t == 5) {
                wg_wait<0>();
                fence_regs(h[0]);
            } else if constexpr (t % 6 == 5) {
                wg_wait<1>();
            } else if constexpr (t == SG_EPI) {
                wg_wait<2>();
                fence_regs(acc2);
            }
            if constexpr (t % 6 == 5) fence_regs(h[((t + 1) / 6) & 1]);
            if constexpr (t == SG_LD && !LAST) mbar_wait(bars + 8 * (B_STG_FULL + 2 * wg), (it + 1) & 1);
            if constexpr (t == SG_OUT) out_ready(LAST || it > 0);
            if constexpr (t == SG_SUM + 1 && !LAST) arrive(B_STG_EMPTY);
            if constexpr (t == (LAST ? 22 : SG_EPI)) mbar_wait(bars + 8 * (B_OUT_FREE + wg), (it & 1) ^ 1);
            constexpr bool g1seg = t % 6 >= 1 && t % 6 <= 3 && (!LAST || t < 18);
            if constexpr (t <= 25 || g1seg) {
                WG_FENCE();
                if constexpr (t <= 25) {
#pragma unroll
                    for (int j = (t == 5 ? 0 : t - 2); j <= t - 2; j++) gemm2_step(acc2, p[j], w2desc, j);
                }
                if constexpr (g1seg) {
                    if constexpr (t == 25) WG_COMMIT();
                    constexpr int c = (t / 6 + 1) % 4;
                    gemm1_step(h[c & 1], a, w1desc, c, (t % 6 - 1) * 2);
                    gemm1_step(h[c & 1], a, w1desc, c, (t % 6 - 1) * 2 + 1);
                }
                WG_COMMIT();
            }
            gelu_upto(Tc, std::integral_constant<int, (LAST ? 24 : 99)>{});
            if constexpr (t >= SG_EPI) {
#pragma unroll
                for (int i = 3 * (t - SG_EPI); i < 3 * (t - SG_EPI) + 3; i++) store_out(i);
            }
            if constexpr (!LAST) layernorm(Tc);
            SCHED_FENCE();
        };
#pragma unroll 1
        for (int it = 0; it < NT / 2 - 1; it++) {
            static_for<5, 29>([&](auto Tc) { segment(Tc, std::false_type{}, it); });
            wg_wait<0>();
        }
        {
            const uint32_t sb2 = __shfl_sync(0xffffffffu, lds32(bars + 8 * B_BASE), 0);
            w1desc = make_desc(sb2 + SM_W1, W1_LBO, W1_SBO);
            w2desc = make_desc(sb2 + SM_W2, W2_LBO, W2_SBO);
        }
        static_for<5, 26>([&](auto Tc) { segment(Tc, std::true_type{}, NT / 2 - 1); });
        wg_wait<0>();
        fence_regs(acc2);
#pragma unroll
        for (int i = 0; i < 6; i++) store_out(i);
        out_ready(true);
        TRS_(4);
    }
}

typedef CUresult (*PFN_encodeTiled)(CUtensorMap*, CUtensorMapDataType, cuuint32_t, void*, const cuuint64_t*,
                                    const cuuint64_t*, const cuuint32_t*, const cuuint32_t*, CUtensorMapInterleave,
                                    CUtensorMapSwizzle, CUtensorMapL2promotion, CUtensorMapFloatOOBfill);

}

extern "C" void kernel_launch(void* const* d_in, const int* in_sizes, int n_in, void* d_out, int out_size) {
    const __nv_bfloat16* x = (const __nv_bfloat16*)d_in[0];
    const __nv_bfloat16* dwl = (const __nv_bfloat16*)d_in[1];
    const __nv_bfloat16* dws = (const __nv_bfloat16*)d_in[2];
    const __nv_bfloat16* w1 = (const __nv_bfloat16*)d_in[3];
    const __nv_bfloat16* w2 = (const __nv_bfloat16*)d_in[4];

    static PFN_encodeTiled encode = nullptr;
    if (!encode) {
        void* fn = nullptr;
        cudaDriverEntryPointQueryResult qres;
        cudaGetDriverEntryPoint("cuTensorMapEncodeTiled", &fn, cudaEnableDefault, &qres);
        encode = (PFN_encodeTiled)fn;
        cudaFuncSetAttribute(fused_block_kernel, cudaFuncAttributeMaxDynamicSharedMemorySize, SMEM_TOTAL);
    }
    CUtensorMap rowmap, copymap, outmap;
    cuuint64_t gdim[3] = {(cuuint64_t)CH, (cuuint64_t)IMG_W, (cuuint64_t)IMG_H};
    cuuint64_t gstride[2] = {(cuuint64_t)PXB, (cuuint64_t)IMG_W * PXB};
    cuuint32_t estr[4] = {1, 1, 1, 1};
    cuuint32_t box_row[3] = {(cuuint32_t)CH, (cuuint32_t)ROW_PX, 2};
    cuuint32_t box_tile[3] = {(cuuint32_t)CH, (cuuint32_t)BW, (cuuint32_t)TR};
    encode(&rowmap, CU_TENSOR_MAP_DATA_TYPE_BFLOAT16, 3, (void*)x, gdim, gstride, box_row, estr,
           CU_TENSOR_MAP_INTERLEAVE_NONE, CU_TENSOR_MAP_SWIZZLE_NONE, CU_TENSOR_MAP_L2_PROMOTION_L2_256B,
           CU_TENSOR_MAP_FLOAT_OOB_FILL_NONE);
    cuuint64_t cdim[4] = {(cuuint64_t)CH, (cuuint64_t)BW, (cuuint64_t)(IMG_W / BW), (cuuint64_t)IMG_H};
    cuuint64_t cstride[3] = {(cuuint64_t)PXB, (cuuint64_t)BW * PXB, (cuuint64_t)IMG_W * PXB};
    cuuint32_t box_copy[4] = {(cuuint32_t)CH, (cuuint32_t)ROW_PX, 1, 2};
    encode(&copymap, CU_TENSOR_MAP_DATA_TYPE_BFLOAT16, 4, d_out, cdim, cstride, box_copy, estr,
           CU_TENSOR_MAP_INTERLEAVE_NONE, CU_TENSOR_MAP_SWIZZLE_NONE, CU_TENSOR_MAP_L2_PROMOTION_NONE,
           CU_TENSOR_MAP_FLOAT_OOB_FILL_NONE);
    encode(&outmap, CU_TENSOR_MAP_DATA_TYPE_BFLOAT16, 3, d_out, gdim, gstride, box_tile, estr,
           CU_TENSOR_MAP_INTERLEAVE_NONE, CU_TENSOR_MAP_SWIZZLE_NONE, CU_TENSOR_MAP_L2_PROMOTION_NONE,
           CU_TENSOR_MAP_FLOAT_OOB_FILL_NONE);
    fused_block_kernel<<<NCTA, NTHREADS, SMEM_TOTAL>>>(rowmap, copymap, outmap, dwl, dws, w1, w2);
}
```

```cpp
#include <cuda_runtime.h>
#include <cuda_bf16.h>
#include <cuda.h>
#include <stdint.h>
#include <type_traits>

#define TRS_(i)

namespace {

constexpr int IMG_H = 512, IMG_W = 512, CH = 96, HID = 384;
constexpr int BW = 16;
constexpr int TR = 4;
constexpr int NT = 32;
constexpr int NCTA = (IMG_W / BW) * (IMG_H / (TR * NT));
constexpr int PXB = CH * 2;
constexpr int ROW_PX = BW + 4;
constexpr int ROW_BYTES = ROW_PX * PXB;
constexpr int UNIT_BYTES = 2 * ROW_BYTES;
constexpr int NU = 2 * NT + 2;
constexpr int STG_PITCH = 208;
constexpr int STG_BYTES = 64 * STG_PITCH;
constexpr int OUT_BYTES = 64 * PXB;
constexpr int NTHREADS = 512;
constexpr int MLP_REGS = 168, TMA_REGS = 24, CONV_REGS = 512 - 2 * MLP_REGS - TMA_REGS;

constexpr int W1_BYTES = CH * HID * 2;
constexpr int W2_BYTES = HID * CH * 2;
constexpr int WPIECE = 24576;
constexpr int SM_W1 = 0;
constexpr int SM_W2 = SM_W1 + W1_BYTES;
constexpr int SM_RING = SM_W2 + W2_BYTES;
constexpr int SM_OUT = SM_RING + 4 * UNIT_BYTES;
constexpr int SM_STG = SM_OUT + 2 * OUT_BYTES;
constexpr int SM_BAR = SM_STG + 2 * STG_BYTES;
constexpr int SMEM_TOTAL = SM_BAR + 256;
static_assert(SMEM_TOTAL <= 232448, "smem");

constexpr int B_RING_FULL = 0;
constexpr int B_RING_EMPTY = 4;
constexpr int B_STG_FULL = 8;
constexpr int B_STG_EMPTY = 12;
constexpr int B_OUT_READY = 14;
constexpr int B_OUT_FREE = 16;
constexpr int B_COPIED = 18;
constexpr int B_FILTER = 19;
constexpr int B_WEIGHTS = 20;
constexpr int B_BASE = 26;

constexpr int W1_LBO = 8 * HID * 2, W1_SBO = 128;
constexpr int W2_KG = 8 * CH * 2;
constexpr int W2_LBO = 8 * W2_KG, W2_SBO = 128;

constexpr float GELU_S = 0.3292034911525734f;
constexpr uint32_t GELU_CH2 = 0x3FC23FC2u, GELU_CL2 = 0x3B513B51u;
constexpr uint32_t GELU_A2 = 0x40D940D9u;

__device__ __forceinline__ uint32_t smem_u32(const void* p) {
    return (uint32_t)__cvta_generic_to_shared(p);
}
__device__ __forceinline__ uint64_t make_desc(uint32_t addr, uint32_t lbo, uint32_t sbo) {
    return (uint64_t)((addr & 0x3FFFF) >> 4) | ((uint64_t)(lbo >> 4) << 16) | ((uint64_t)(sbo >> 4) << 32);
}
__device__ __forceinline__ void mbar_init(uint32_t bar, uint32_t cnt) {
    asm volatile("mbarrier.init.shared::cta.b64 [%0], %1;" ::"r"(bar), "r"(cnt));
}
__device__ __forceinline__ void mbar_expect_tx(uint32_t bar, uint32_t bytes) {
    asm volatile("mbarrier.arrive.expect_tx.shared::cta.b64 _, [%0], %1;" ::"r"(bar), "r"(bytes) : "memory");
}
__device__ __forceinline__ void mbar_arrive_if(uint32_t bar, bool pred) {
    asm volatile("{\n.reg .pred p;\nsetp.ne.u32 p, %1, 0;\n@p mbarrier.arrive.shared::cta.b64 _, [%0];\n}\n"
                 ::"r"(bar), "r"((uint32_t)pred) : "memory");
}
__device__ __forceinline__ void mbar_wait(uint32_t bar, uint32_t parity) {
    asm volatile(
        "{\n"
        ".reg .pred p;\n"
        "WAIT_LOOP:\n"
        "mbarrier.try_wait.parity.shared::cta.b64 p, [%0], %1, %2;\n"
        "@p bra WAIT_DONE;\n"
        "bra WAIT_LOOP;\n"
        "WAIT_DONE:\n"
        "}\n" ::"r"(bar), "r"(parity), "r"(20000) : "memory");
}
__device__ __forceinline__ void tma_load3d(uint32_t dst, const CUtensorMap* map, int cx, int cy, uint32_t bar) {
    asm volatile(
        "cp.async.bulk.tensor.3d.shared::cluster.global.mbarrier::complete_tx::bytes [%0], [%1, {%2, %3, %4}], [%5];"
        ::"r"(dst), "l"((uint64_t)map), "r"(0), "r"(cx), "r"(cy), "r"(bar) : "memory");
}
__device__ __forceinline__ void bulk_load(uint32_t dst, const void* src, uint32_t bytes, uint32_t bar) {
    asm volatile("cp.async.bulk.shared::cluster.global.mbarrier::complete_tx::bytes [%0], [%1], %2, [%3];"
                 ::"r"(dst), "l"(src), "r"(bytes), "r"(bar) : "memory");
}
__device__ __forceinline__ uint4 lds128(uint32_t addr) {
    uint4 v;
    asm volatile("ld.shared.v4.u32 {%0,%1,%2,%3}, [%4];" : "=r"(v.x), "=r"(v.y), "=r"(v.z), "=r"(v.w) : "r"(addr));
    return v;
}
__device__ __forceinline__ uint32_t lds32(uint32_t addr) {
    uint32_t v;
    asm volatile("ld.shared.u32 %0, [%1];" : "=r"(v) : "r"(addr));
    return v;
}
__device__ __forceinline__ void sts128(uint32_t addr, uint4 v) {
    asm volatile("st.shared.v4.u32 [%0], {%1,%2,%3,%4};" ::"r"(addr), "r"(v.x), "r"(v.y), "r"(v.z), "r"(v.w) : "memory");
}
__device__ __forceinline__ void sts32(uint32_t addr, uint32_t a) {
    asm volatile("st.shared.u32 [%0], %1;" ::"r"(addr), "r"(a) : "memory");
}
__device__ __forceinline__ void ldsm4(uint32_t& a, uint32_t& b, uint32_t& c, uint32_t& d, uint32_t addr) {
    asm volatile("ldmatrix.sync.aligned.m8n8.x4.shared.b16 {%0,%1,%2,%3}, [%4];"
                 : "=r"(a), "=r"(b), "=r"(c), "=r"(d) : "r"(addr));
}
__device__ __forceinline__ void ldsm2(uint32_t& a, uint32_t& b, uint32_t addr) {
    asm volatile("ldmatrix.sync.aligned.m8n8.x2.shared.b16 {%0,%1}, [%2];" : "=r"(a), "=r"(b) : "r"(addr));
}
__device__ __forceinline__ void stsm4(uint32_t addr, uint32_t a, uint32_t b, uint32_t c, uint32_t d) {
    asm volatile("stmatrix.sync.aligned.m8n8.x4.shared.b16 [%0], {%1,%2,%3,%4};"
                 ::"r"(addr), "r"(a), "r"(b), "r"(c), "r"(d) : "memory");
}
__device__ __forceinline__ void stsm2(uint32_t addr, uint32_t a, uint32_t b) {
    asm volatile("stmatrix.sync.aligned.m8n8.x2.shared.b16 [%0], {%1,%2};" ::"r"(addr), "r"(a), "r"(b) : "memory");
}
__device__ __forceinline__ uint32_t hfma2(uint32_t a, uint32_t b, uint32_t c) {
    uint32_t d;
    asm("fma.rn.bf16x2 %0, %1, %2, %3;" : "=r"(d) : "r"(a), "r"(b), "r"(c));
    return d;
}
__device__ __forceinline__ uint32_t hmul2(uint32_t a, uint32_t b) {
    uint32_t d;
    asm("mul.rn.bf16x2 %0, %1, %2;" : "=r"(d) : "r"(a), "r"(b));
    return d;
}
__device__ __forceinline__ uint32_t hadd2(uint32_t a, uint32_t b) {
    uint32_t d;
    asm("add.rn.bf16x2 %0, %1, %2;" : "=r"(d) : "r"(a), "r"(b));
    return d;
}
__device__ __forceinline__ uint32_t hsub2(uint32_t a, uint32_t b) {
    uint32_t d;
    asm("sub.rn.bf16x2 %0, %1, %2;" : "=r"(d) : "r"(a), "r"(b));
    return d;
}
__device__ __forceinline__ uint32_t fold(uint32_t a, uint32_t b) {
    return hadd2(__byte_perm(a, b, 0x5410), __byte_perm(a, b, 0x7632));
}
__device__ __forceinline__ float bf_lo(uint32_t v) { return __uint_as_float(v << 16); }
__device__ __forceinline__ float bf_hi(uint32_t v) { return __uint_as_float(v & 0xffff0000u); }
__device__ __forceinline__ uint32_t pack_bf16(float lo, float hi) {
    uint32_t d;
    asm("cvt.rn.bf16x2.f32 %0, %1, %2;" : "=r"(d) : "f"(hi), "f"(lo));
    return d;
}
__device__ __forceinline__ uint32_t pack_f16(float lo, float hi) {
    uint32_t d;
    asm("cvt.rn.f16x2.f32 %0, %1, %2;" : "=r"(d) : "f"(hi), "f"(lo));
    return d;
}
__device__ __forceinline__ uint32_t bf2h(uint32_t v) { return pack_f16(bf_lo(v), bf_hi(v)); }
__device__ __forceinline__ uint4 bf2h4(uint4 v) { return make_uint4(bf2h(v.x), bf2h(v.y), bf2h(v.z), bf2h(v.w)); }
__device__ __forceinline__ uint32_t mulc(uint32_t v) { return hfma2(v, GELU_CH2, hmul2(v, GELU_CL2)); }
__device__ __forceinline__ uint32_t h2bf(uint32_t h) {
    float lo, hi;
    asm("{\n.reg .b16 l, h;\nmov.b32 {l, h}, %2;\ncvt.f32.f16 %0, l;\ncvt.f32.f16 %1, h;\n}\n" : "=f"(lo), "=f"(hi) : "r"(h));
    return pack_bf16(lo, hi);
}

#define WG_FENCE() asm volatile("wgmma.fence.sync.aligned;" ::: "memory")
#define WG_COMMIT() asm volatile("wgmma.commit_group.sync.aligned;" ::: "memory")
template <int N>
__device__ __forceinline__ void wg_wait() {
    asm volatile("wgmma.wait_group.sync.aligned %0;" ::"n"(N) : "memory");
}
#define SCHED_FENCE() asm volatile("pmevent.mask 0;" ::: "memory")

template <bool ACC>
__device__ __forceinline__ void wgmma_rs(uint32_t (&d)[24], const uint32_t (&a)[4], uint64_t desc) {
    asm volatile(
        "{\n"
        ".reg .pred p;\n"
        "setp.ne.b32 p, %29, 0;\n"
        "wgmma.mma_async.sync.aligned.m64n96k16.f16.f16.f16 {"
        "%0,%1,%2,%3,%4,%5,%6,%7,%8,%9,%10,%11,%12,%13,%14,%15,"
        "%16,%17,%18,%19,%20,%21,%22,%23"
        "}, {%24,%25,%26,%27}, %28, p, 1, 1, 1;\n"
        "}\n"
        : "+r"(d[0]), "+r"(d[1]), "+r"(d[2]), "+r"(d[3]), "+r"(d[4]), "+r"(d[5]), "+r"(d[6]), "+r"(d[7]),
          "+r"(d[8]), "+r"(d[9]), "+r"(d[10]), "+r"(d[11]), "+r"(d[12]), "+r"(d[13]), "+r"(d[14]), "+r"(d[15]),
          "+r"(d[16]), "+r"(d[17]), "+r"(d[18]), "+r"(d[19]), "+r"(d[20]), "+r"(d[21]), "+r"(d[22]), "+r"(d[23])
        : "r"(a[0]), "r"(a[1]), "r"(a[2]), "r"(a[3]), "l"(desc), "n"(ACC ? 1 : 0));
}
__device__ __forceinline__ void gemm1_step(uint32_t (&h)[24], const uint32_t (&a)[6][4], uint64_t w1desc, int c, int ks) {
    const uint64_t d = w1desc + (uint64_t)((c * 12 * W1_SBO + ks * 2 * W1_LBO) >> 4);
    if (ks == 0) wgmma_rs<false>(h, a[0], d);
    else wgmma_rs<true>(h, a[ks], d);
}
__device__ __forceinline__ void gemm2_step(uint32_t (&acc2)[24], const uint32_t (&p)[4], uint64_t w2desc, int j) {
    const uint64_t d = w2desc + (uint64_t)(((16 * (j % 3) + j / 3) * W2_KG) >> 4);
    if (j == 0) wgmma_rs<false>(acc2, p, d);
    else wgmma_rs<true>(acc2, p, d);
}
__device__ __forceinline__ uint32_t gelu_front(uint32_t y) {
    uint32_t t, u;
    asm("fma.rn.f16x2 %0, %1, %1, %2;" : "=r"(t) : "r"(y), "r"(GELU_A2));
    asm("mul.rn.f16x2 %0, %1, %2;" : "=r"(u) : "r"(y), "r"(t));
    return u;
}
__device__ __forceinline__ void gelu_tanh(uint16_t& lo, uint16_t& hi, uint32_t u) {
    asm("{\n.reg .b16 l, h;\nmov.b32 {l, h}, %2;\ntanh.approx.f16 %0, l;\ntanh.approx.f16 %1, h;\n}\n"
        : "=h"(lo), "=h"(hi) : "r"(u));
}
__device__ __forceinline__ uint32_t gelu_back(uint32_t y, uint16_t lo, uint16_t hi) {
    uint32_t g;
    asm("{\n.reg .b32 t;\nmov.b32 t, {%2, %3};\nfma.rn.f16x2 %0, %1, t, %1;\n}\n" : "=r"(g) : "r"(y), "h"(lo), "h"(hi));
    return g;
}

template <int B, int E, typename F>
__device__ __forceinline__ void static_for(F&& f) {
    if constexpr (B < E) {
        f(std::integral_constant<int, B>{});
        static_for<B + 1, E>(f);
    }
}

template <int NP, int R0, int R1 = 5>
__device__ __forceinline__ void conv_row(uint32_t (&o)[2 * NP], uint32_t (&acc)[4][NP][3], const uint32_t (&w)[5][7],
                                         const uint32_t (&x)[2 * NP + 4]) {
    uint32_t e[NP + 1], f[NP + 1], t[5][NP][3];
#pragma unroll
    for (int i = 0; i <= NP; i++) {
        e[i] = hsub2(x[2 * i], x[2 * i + 1]);
        f[i] = hsub2(x[2 * i + 2], x[2 * i + 1]);
    }
#pragma unroll
    for (int p = 0; p < NP; p++) {
#pragma unroll
        for (int r = R0; r < R1; r++) {
            const uint32_t(&h)[7] = w[4 - r];
            t[r][p][1] = r < 4 ? hfma2(x[2 * p + 1], h[3], acc[r & 3][p][1]) : hmul2(x[2 * p + 1], h[3]);
            t[r][p][0] = r < 4 ? hfma2(x[2 * p + 4], h[2], acc[r & 3][p][0]) : hmul2(x[2 * p + 4], h[2]);
            t[r][p][2] = r < 4 ? hfma2(x[2 * p + 5], h[2], acc[r & 3][p][2]) : hmul2(x[2 * p + 5], h[2]);
        }
#pragma unroll
        for (int r = R0; r < R1; r++) {
            const uint32_t(&h)[7] = w[4 - r];
            t[r][p][1] = hfma2(x[2 * p + 3], h[4], t[r][p][1]);
            t[r][p][0] = hfma2(e[p], h[0], t[r][p][0]);
            t[r][p][2] = hfma2(f[p], h[5], t[r][p][2]);
        }
#pragma unroll
        for (int r = R0; r < R1; r++) {
            const uint32_t(&h)[7] = w[4 - r];
            t[r][p][0] = hfma2(e[p + 1], h[1], t[r][p][0]);
            t[r][p][2] = hfma2(f[p + 1], h[6], t[r][p][2]);
        }
        if (R0 == 0) {
            o[2 * p] = hadd2(t[0][p][0], t[0][p][1]);
            o[2 * p + 1] = hadd2(t[0][p][1], t[0][p][2]);
        }
#pragma unroll
        for (int r = (R0 > 0 ? R0 : 1); r < R1; r++)
#pragma unroll
            for (int m = 0; m < 3; m++) acc[r - 1][p][m] = t[r][p][m];
    }
}

constexpr int SG_LD = 11, SG_S0 = 12, SG_SUM = 14, SG_SH2 = 15, SG_RS = 16, SG_CVT = 18;
constexpr int SG_OUT = 6;
constexpr int SG_EPI = 27;

__global__ void __launch_bounds__(NTHREADS, 1)
fused_block_kernel(const __grid_constant__ CUtensorMap rowmap, const __grid_constant__ CUtensorMap copymap,
                   const __grid_constant__ CUtensorMap outmap,
                   const __nv_bfloat16* __restrict__ dwl, const __nv_bfloat16* __restrict__ dws,
                   const __nv_bfloat16* __restrict__ w1, const __nv_bfloat16* __restrict__ w2) {
    extern __shared__ __align__(1024) uint8_t smem[];
    const uint32_t sbase = smem_u32(smem);
    const int tid = threadIdx.x;
    const int wid = __shfl_sync(0xffffffffu, tid >> 5, 0) ^ 8;
    const int wg = wid >> 2, warp = wid & 3;
    const int lane = tid & 31;
    const uint32_t bars = sbase + SM_BAR;
    const int x0 = (blockIdx.x >> 2) * BW, y0 = (blockIdx.x & 3) * (TR * NT);

    if (tid == NTHREADS - 128) {
        const char* w1b = reinterpret_cast<const char*>(w1);
        const char* w2b = reinterpret_cast<const char*>(w2);
        asm volatile("cp.async.bulk.prefetch.L2.global [%0], %1;"
                     ::"l"(((blockIdx.x & 1) ? w2b : w1b) + (blockIdx.x >> 1) * (W1_BYTES / (NCTA / 2))), "r"(W1_BYTES / (NCTA / 2))
                     : "memory");
        mbar_init(bars + 8 * B_FILTER, 1);
#pragma unroll
        for (int i = 0; i < 4; i++) mbar_init(bars + 8 * (B_RING_FULL + i), 1);
#pragma unroll
        for (int i = 0; i < 6; i++) mbar_init(bars + 8 * (B_WEIGHTS + i), 1);
        asm volatile("fence.mbarrier_init.release.cluster;" ::: "memory");
        auto rows = [&](int u) {
            mbar_expect_tx(bars + 8 * (B_RING_FULL + u), UNIT_BYTES);
            tma_load3d(sbase + SM_RING + u * UNIT_BYTES, &rowmap, x0 - 2, y0 - 2 + 2 * u, bars + 8 * (B_RING_FULL + u));
        };
        auto weights = [&](int i) {
            mbar_expect_tx(bars + 8 * (B_WEIGHTS + i), WPIECE);
            bulk_load(sbase + i * WPIECE, (i < 3 ? w1b : w2b) + (i % 3) * WPIECE, WPIECE, bars + 8 * (B_WEIGHTS + i));
        };
        weights(0);
        mbar_expect_tx(bars + 8 * B_FILTER, 34 * PXB);
        bulk_load(sbase + SM_OUT, dws, 25 * PXB, bars + 8 * B_FILTER);
        bulk_load(sbase + SM_OUT + 25 * PXB, dwl, 9 * PXB, bars + 8 * B_FILTER);
        rows(0); rows(1);
        weights(1); weights(2);
        rows(2); rows(3);
        weights(3); weights(4); weights(5);
    } else if (tid == NTHREADS - 96) {
#pragma unroll
        for (int m = 0; m < 2; m++) {
            mbar_init(bars + 8 * (B_RING_EMPTY + 2 * m), 4);
            mbar_init(bars + 8 * (B_RING_EMPTY + 2 * m + 1), 4);
            mbar_init(bars + 8 * (B_STG_FULL + 2 * m), 4);
            mbar_init(bars + 8 * (B_STG_EMPTY + m), 4);
            mbar_init(bars + 8 * (B_OUT_READY + m), 4);
            mbar_init(bars + 8 * (B_OUT_FREE + m), 1);
        }
        mbar_init(bars + 8 * B_COPIED, 2);
        sts32(bars + 8 * B_BASE, sbase);
        asm volatile("fence.mbarrier_init.release.cluster;" ::: "memory");
    }
    __syncthreads();

    if (wg == 3) {
        asm volatile("setmaxnreg.dec.sync.aligned.u32 %0;" ::"n"(TMA_REGS));
        const int m = warp >> 1;
        if (lane == 0) {
            if (warp == 0 || warp == 3) {
#pragma unroll 1
                for (int u = 2 * m; u < NU - 1; u += (u & 1) ? 3 : 1) {
                    const uint32_t fb = bars + 8 * (B_RING_FULL + (u & 3)), buf = sbase + SM_RING + (u & 3) * UNIT_BYTES;
                    mbar_wait(bars + 8 * (B_RING_EMPTY + (u & 3)), (u >> 2) & 1);
                    if (u != 0) {
                        asm volatile("cp.async.bulk.tensor.4d.global.shared::cta.bulk_group [%0, {%1, %2, %3, %4}], [%5];"
                                     ::"l"((uint64_t)&copymap), "r"(0), "r"(0), "r"(blockIdx.x >> 2), "r"(y0 - 2 + 2 * u),
                                     "r"(buf + 2 * PXB) : "memory");
                        asm volatile("cp.async.bulk.commit_group;" ::: "memory");
                        asm volatile("cp.async.bulk.wait_group 0;" ::: "memory");
                    }
                    if (u + 4 < NU) {
                        mbar_expect_tx(fb, UNIT_BYTES);
                        tma_load3d(buf, &rowmap, x0 - 2, y0 + 6 + 2 * u, fb);
                    }
                }
                mbar_arrive_if(bars + 8 * B_COPIED, true);
            } else {
                const uint32_t buf = sbase + SM_OUT + m * OUT_BYTES;
#pragma unroll 1
                for (int i = 0; i < NT / 2; i++) {
                    if (i == NT / 2 - 1) mbar_wait(bars + 8 * B_COPIED, 0);
                    mbar_wait(bars + 8 * (B_OUT_READY + m), i & 1);
                    asm volatile("cp.reduce.async.bulk.tensor.3d.global.shared::cta.add.bulk_group [%0, {%1, %2, %3}], [%4];"
                                 ::"l"((uint64_t)&outmap), "r"(0), "r"(x0), "r"(y0 + TR * (2 * i + m)), "r"(buf) : "memory");
                    asm volatile("cp.async.bulk.commit_group;" ::: "memory");
                    asm volatile("cp.async.bulk.wait_group 0;" ::: "memory");
                    mbar_arrive_if(bars + 8 * (B_OUT_FREE + m), true);
                }
            }
        }
    } else if (wg == 2) {
        asm volatile("setmaxnreg.inc.sync.aligned.u32 %0;" ::"n"(CONV_REGS));
        uint32_t wa[5][7], wb[5][7];
        {
            const uint32_t pa = sbase + SM_OUT + 4 * lane, pb = sbase + SM_OUT + 4 * (32 + (lane & 15));
            const bool mir = lane >= 16;
            mbar_wait(bars + 8 * B_FILTER, 0);
#pragma unroll
            for (int r = 0; r < 5; r++) {
                uint32_t u[5], v[5];
#pragma unroll
                for (int c = 0; c < 5; c++) {
                    u[c] = lds32(pa + (5 * r + c) * PXB);
                    v[c] = lds32(pb + (5 * r + c) * PXB);
                    if (r >= 1 && r <= 3 && c >= 1 && c <= 3) {
                        u[c] = hadd2(u[c], lds32(pa + (25 + 3 * (r - 1) + c - 1) * PXB));
                        v[c] = hadd2(v[c], lds32(pb + (25 + 3 * (r - 1) + c - 1) * PXB));
                    }
                }
#pragma unroll
                for (int c = 0; c < 2; c++) {
                    const uint32_t lo = v[c], hi = v[4 - c];
                    v[c] = mir ? hi : lo;
                    v[4 - c] = mir ? lo : hi;
                }
                wa[r][0] = u[0]; wa[r][1] = u[2]; wa[r][2] = u[4]; wa[r][3] = hadd2(u[0], u[1]);
                wa[r][4] = hadd2(u[2], u[3]); wa[r][5] = u[1]; wa[r][6] = u[3];
                wb[r][0] = v[0]; wb[r][1] = v[2]; wb[r][2] = v[4]; wb[r][3] = hadd2(v[0], v[1]);
                wb[r][4] = hadd2(v[2], v[3]); wb[r][5] = v[1]; wb[r][6] = v[3];
            }
        }
        const int mi = lane >> 3, mr = lane & 7, up = mr >> 2;
        const uint32_t ring_a = sbase + SM_RING + (4 * warp + mi) * PXB + mr * 16;
        const uint32_t ring_b0 = sbase + SM_RING + (4 * warp + (up ? 7 - mi : mi)) * PXB + 128 + (mr & 3) * 16;
        const uint32_t ring_b1 = sbase + SM_RING + (4 * warp + (up ? 3 - mi : 4 + mi)) * PXB + 128 + (mr & 3) * 16;
        const uint32_t stg_a = sbase + SM_STG + (4 * warp + mi) * STG_PITCH + mr * 16;
        const uint32_t stg_b = sbase + SM_STG + (4 * warp + (up ? 3 - mi : mi)) * STG_PITCH + 128 + (mr & 3) * 16;
        uint32_t acca[4][2][3], accb[4][1][3], xa[8], xb[6], oa[4], ob[2];
        auto fetch_a = [&](uint32_t off) {
            ldsm4(xa[0], xa[1], xa[2], xa[3], ring_a + off);
            ldsm4(xa[4], xa[5], xa[6], xa[7], ring_a + off + 4 * PXB);
        };
        auto fetch_b = [&](uint32_t off) {
            ldsm4(xb[0], xb[1], xb[2], xb[3], ring_b0 + off);
            ldsm2(xb[4], xb[5], ring_b1 + off);
        };
        const uint32_t arr = bars + 8 * (lane == 0 ? B_RING_EMPTY + 3 : B_STG_FULL);
        TRS_(0);
        static_for<0, 4>([&](auto Rc) {
            constexpr int R = decltype(Rc)::value;
            if (R % 2 == 0) mbar_wait(bars + 8 * (B_RING_FULL + R / 2), 0);
            fetch_a(R * ROW_BYTES);
            fetch_b(R * ROW_BYTES);
            conv_row<2, 4 - R>(oa, acca, wa, xa);
            conv_row<1, 4 - R>(ob, accb, wb, xb);
        });
        SCHED_FENCE();
        __syncwarp();
        mbar_arrive_if(bars + 8 * (B_RING_EMPTY + lane), lane < 2);
        mbar_wait(bars + 8 * (B_RING_FULL + 2), 0);
        fetch_a(4 * ROW_BYTES);
        fetch_b(4 * ROW_BYTES);
        TRS_(5);
        auto tile = [&](auto Sc, auto Lc, uint32_t ph) {
            constexpr int s = decltype(Sc)::value;
            constexpr bool LAST = decltype(Lc)::value;
            static_for<0, 4>([&](auto Rc) {
                constexpr int R = decltype(Rc)::value, R1 = LAST ? 4 - R : 5;
                constexpr int nrow = (4 * (s ^ 1) + R + 1) & 7;
                constexpr bool more = !LAST || R < 3;
                constexpr uint32_t dst = s * STG_BYTES + R * (BW * STG_PITCH);
                conv_row<2, 0, R1>(oa, acca, wa, xa);
                if (R == 0) mbar_wait(bars + 8 * (B_STG_EMPTY + s), ph ^ 1);
                if ((R & 1) && more) mbar_wait(bars + 8 * (B_RING_FULL + nrow / 2), (s == 0 && R == 1) ? ph : ph ^ 1);
                if (more) fetch_a(nrow * ROW_BYTES);
                stsm4(stg_a + dst, oa[0], oa[1], oa[2], oa[3]);
                conv_row<1, 0, R1>(ob, accb, wb, xb);
                if (more) fetch_b(nrow * ROW_BYTES);
                stsm2(stg_b + dst, ob[0], ob[1]);
                if (R & 1) __syncwarp();
                if (R == 1) mbar_arrive_if(bars + 8 * (B_RING_EMPTY + 2 * (s ^ 1)), lane == 0);
                if (R == 3) mbar_arrive_if(arr ^ (16 * s), lane < 2);
                if (R < 3 || s == 0) SCHED_FENCE();
            });
        };
#pragma unroll 1
        for (int k = 0; k < NT / 2 - 1; k++) {
            tile(std::integral_constant<int, 0>{}, std::false_type{}, k & 1);
            tile(std::integral_constant<int, 1>{}, std::false_type{}, k & 1);
        }
        SCHED_FENCE();
        tile(std::integral_constant<int, 0>{}, std::false_type{}, (NT / 2 - 1) & 1);
        tile(std::integral_constant<int, 1>{}, std::true_type{}, (NT / 2 - 1) & 1);
        TRS_(4);
    } else {
        asm volatile("setmaxnreg.inc.sync.aligned.u32 %0;" ::"n"(MLP_REGS));
        TRS_(0);
        {
            const int kk = lane & 7, a0 = (kk + (lane >> 3)) & 7;
#pragma unroll 1
            for (int t = wid; t < 24; t += 8) {
                const uint32_t base = sbase + SM_W1 + (t >> 1) * W1_LBO + (t & 1) * 384;
                uint4 v[6];
                mbar_wait(bars + 8 * (B_WEIGHTS + (t >> 3)), 0);
#pragma unroll
                for (int i = 0; i < 6; i++) v[i] = lds128(base + (i >> 1) * 128 + kk * (HID * 2) + (a0 ^ ((i & 1) * 4)) * 16);
                __syncwarp();
#pragma unroll
                for (int i = 0; i < 6; i++)
                    sts128(base + (i >> 1) * 128 + (a0 ^ ((i & 1) * 4)) * (HID * 2) + kk * 16, bf2h4(v[i]));
            }
            asm volatile("fence.proxy.async.shared::cta;" ::: "memory");
            asm volatile("bar.sync 1, 256;" ::: "memory");
            TRS_(1);
            const uint32_t src = sbase + SM_W2 + (lane >> 2) * (CH * 2) + (lane & 3) * 16, dst = sbase + SM_W2 + lane * 16;
#pragma unroll 1
            for (int t = wg ? 16 + warp : warp; t < (wg ? 48 : 16); t += 4) {
                uint4 v[3];
                mbar_wait(bars + 8 * (B_WEIGHTS + 3 + (t >> 4)), 0);
#pragma unroll
                for (int i = 0; i < 3; i++) v[i] = lds128(src + t * W2_KG + i * 64);
                __syncwarp();
#pragma unroll
                for (int i = 0; i < 3; i++) {
                    const uint4 c = bf2h4(make_uint4(mulc(v[i].x), mulc(v[i].y), mulc(v[i].z), mulc(v[i].w)));
                    stsm4(dst + t * W2_KG + i * 512, c.x, c.y, c.z, c.w);
                }
            }
            asm volatile("fence.proxy.async.shared::cta;" ::: "memory");
            asm volatile("bar.arrive %0, 256;" ::"r"(2 + wg) : "memory");
            TRS_(2);
        }

        uint64_t w1desc = make_desc(sbase + SM_W1, W1_LBO, W1_SBO);
        uint64_t w2desc = make_desc(sbase + SM_W2, W2_LBO, W2_SBO);
        const uint32_t ldm_addr = sbase + SM_STG + wg * STG_BYTES +
                                  (16 * warp + (lane & 7) + ((lane >> 3) & 1) * 8) * STG_PITCH + (lane >> 4) * 16;
        const uint32_t out_addr = sbase + SM_OUT + wg * OUT_BYTES + (16 * warp + (lane >> 2)) * PXB + (lane & 3) * 16;

        uint32_t a[6][4], r[6][4];
        uint32_t h[2][24], acc2[24];
        uint32_t p[24][4], u[2][4];
        uint16_t tl[2][4], tg[2][4];
        uint32_t ps[2], sq[4], rp[2], cp[2], st[2], sx[2];
        auto fence_regs = [&](auto& v) {
#pragma unroll
            for (int i = 0; i < (int)(sizeof(v) / 4); i++) asm volatile("" : "+r"(v[i]) :: "memory");
        };
#pragma unroll
        for (int i = 0; i < 24; i++) acc2[i] = h[0][i] = h[1][i] = 0u;
        fence_regs(acc2);
        fence_regs(h[0]);
        fence_regs(h[1]);

        auto layernorm = [&](auto Tc) {
            constexpr int t = decltype(Tc)::value;
            if constexpr (t == SG_LD || t == SG_LD + 1) {
#pragma unroll
                for (int ks = 3 * (t - SG_LD); ks < 3 * (t - SG_LD) + 3; ks++)
                    ldsm4(r[ks][0], r[ks][1], r[ks][2], r[ks][3], ldm_addr + ks * 32);
            }
            if constexpr (t >= SG_S0 && t <= SG_SUM) {
                constexpr int k0 = 2 * (t - SG_S0);
#pragma unroll
                for (int j = 0; j < 2; j++) {
                    const uint32_t v = hadd2(hadd2(r[k0][j], r[k0][j + 2]), hadd2(r[k0 + 1][j], r[k0 + 1][j + 2]));
                    ps[j] = k0 == 0 ? v : hadd2(ps[j], v);
                }
#pragma unroll
                for (int ks = k0; ks < k0 + 2; ks++)
#pragma unroll
                    for (int j = 0; j < 4; j++)
                        sq[j] = ks == 0 ? hmul2(r[ks][j], r[ks][j]) : hfma2(r[ks][j], r[ks][j], sq[j]);
            }
            if constexpr (t == SG_SUM) {
                st[0] = fold(ps[0], ps[1]);
                st[1] = fold(hadd2(sq[0], sq[2]), hadd2(sq[1], sq[3]));
#pragma unroll
                for (int i = 0; i < 2; i++) sx[i] = __shfl_xor_sync(0xffffffffu, st[i], 1);
            }
            if constexpr (t == SG_SH2) {
#pragma unroll
                for (int i = 0; i < 2; i++) {
                    st[i] = hadd2(st[i], sx[i]);
                    sx[i] = __shfl_xor_sync(0xffffffffu, st[i], 2);
                }
            }
            if constexpr (t == SG_RS) {
                const uint32_t s1 = hadd2(st[0], sx[0]), s2 = hadd2(st[1], sx[1]);
                float nm[2], var[2];
                bool poor = false;
#pragma unroll
                for (int j = 0; j < 2; j++) {
                    nm[j] = (j ? bf_hi(s1) : bf_lo(s1)) * (-1.0f / CH);
                    const float m2 = nm[j] * nm[j];
                    var[j] = fmaf(j ? bf_hi(s2) : bf_lo(s2), 1.0f / CH, -m2);
                    poor |= !(4.0f * m2 <= var[j]);
                }
                if (__any_sync(0xffffffffu, poor)) {
                    uint32_t d1[4], d2[4];
#pragma unroll
                    for (int j = 0; j < 4; j++) {
                        const uint32_t c = pack_bf16(nm[j & 1], nm[j & 1]);
#pragma unroll
                        for (int ks = 0; ks < 6; ks++) {
                            r[ks][j] = hadd2(r[ks][j], c);
                            d1[j] = ks == 0 ? r[ks][j] : hadd2(d1[j], r[ks][j]);
                            d2[j] = ks == 0 ? hmul2(r[ks][j], r[ks][j]) : hfma2(r[ks][j], r[ks][j], d2[j]);
                        }
                    }
                    uint32_t v1 = fold(hadd2(d1[0], d1[2]), hadd2(d1[1], d1[3]));
                    uint32_t v2 = fold(hadd2(d2[0], d2[2]), hadd2(d2[1], d2[3]));
#pragma unroll
                    for (int i = 1; i <= 2; i++) {
                        v1 = hadd2(v1, __shfl_xor_sync(0xffffffffu, v1, i));
                        v2 = hadd2(v2, __shfl_xor_sync(0xffffffffu, v2, i));
                    }
#pragma unroll
                    for (int j = 0; j < 2; j++) {
                        nm[j] = (j ? bf_hi(v1) : bf_lo(v1)) * (-1.0f / CH);
                        var[j] = fmaxf(fmaf(j ? bf_hi(v2) : bf_lo(v2), 1.0f / CH, -nm[j] * nm[j]), 0.f);
                    }
                }
#pragma unroll
                for (int j = 0; j < 2; j++) {
                    constexpr float K = 1.0f / (GELU_S * GELU_S);
                    float rs;
                    asm("rsqrt.approx.ftz.f32 %0, %1;" : "=f"(rs) : "f"(fmaf(var[j], K, K * 1e-5f)));
                    rp[j] = pack_bf16(rs, rs);
                    const float c = nm[j] * bf_lo(rp[j]);
                    cp[j] = pack_bf16(c, c);
                }
            }
            if constexpr (t >= SG_CVT && t < SG_CVT + 3) {
#pragma unroll
                for (int ks = 2 * (t - SG_CVT); ks < 2 * (t - SG_CVT) + 2; ks++)
#pragma unroll
                    for (int j = 0; j < 4; j++) a[ks][j] = bf2h(hfma2(r[ks][j], rp[j & 1], cp[j & 1]));
            }
        };
        auto gelu_upto = [&](auto Tc, auto Ec) {
            constexpr int t = decltype(Tc)::value, END = decltype(Ec)::value;
            constexpr int sf = (t + 1) % 24, sb = (t + 23) % 24;
            if constexpr (t >= 0 && t < END) {
#pragma unroll
                for (int i = 0; i < 4; i++) gelu_tanh(tl[t & 1][i], tg[t & 1][i], u[t & 1][i]);
            }
            if constexpr (t + 1 < END) {
#pragma unroll
                for (int i = 0; i < 4; i++) u[(t + 1) & 1][i] = gelu_front(h[(sf / 6) & 1][4 * (sf % 6) + i]);
            }
            if constexpr (t >= 1 && t - 1 < END) {
#pragma unroll
                for (int i = 0; i < 4; i++)
                    p[sb][i] = gelu_back(h[(sb / 6) & 1][4 * (sb % 6) + i], tl[(t + 1) & 1][i], tg[(t + 1) & 1][i]);
            }
        };
        auto gelu = [&](auto Tc) { gelu_upto(Tc, std::integral_constant<int, 99>{}); };
        auto arrive = [&](int bar) {
            __syncwarp();
            mbar_arrive_if(bars + 8 * (bar + wg), lane == 0);
        };
        auto store_out = [&](int i) {
            const int half = i / 3, j = i % 3;
            sts128(out_addr + half * 8 * PXB + j * 64,
                   make_uint4(h2bf(acc2[8 * j + half]), h2bf(acc2[8 * j + 2 + half]), h2bf(acc2[8 * j + 4 + half]),
                              h2bf(acc2[8 * j + 6 + half])));
        };
        auto out_ready = [&](bool pred) {
            asm volatile("fence.proxy.async.shared::cta;" ::: "memory");
            __syncwarp();
            mbar_arrive_if(bars + 8 * (B_OUT_READY + wg), pred && lane == 0);
        };

        mbar_wait(bars + 8 * (B_STG_FULL + 2 * wg), 0);
        TRS_(3);
        static_for<SG_LD, SG_CVT + 3>(layernorm);
        SCHED_FENCE();
        arrive(B_STG_EMPTY);
        WG_FENCE();
#pragma unroll
        for (int ks = 0; ks < 6; ks++) gemm1_step(h[0], a, w1desc, 0, ks);
        WG_COMMIT();
#pragma unroll
        for (int ks = 0; ks < 6; ks++) gemm1_step(h[1], a, w1desc, 1, ks);
        WG_COMMIT();
        wg_wait<1>();
        fence_regs(h[0]);
        static_for<-1, 5>(gelu);
        wg_wait<0>();
        asm volatile("bar.sync %0, 256;" ::"r"(3 - wg) : "memory");
        asm volatile("bar.sync %0, 128;" ::"r"(4 + wg) : "memory");

        auto segment = [&](auto Tc, auto Lc, int it) {
            constexpr int t = decltype(Tc)::value;
            constexpr bool LAST = decltype(Lc)::value;
            if constexpr (t == 5) {
                wg_wait<0>();
                fence_regs(h[0]);
            } else if constexpr (t % 6 == 5) {
                wg_wait<1>();
            } else if constexpr (t == SG_EPI) {
                wg_wait<2>();
                fence_regs(acc2);
            }
            if constexpr (t % 6 == 5) fence_regs(h[((t + 1) / 6) & 1]);
            if constexpr (t == SG_LD && !LAST) mbar_wait(bars + 8 * (B_STG_FULL + 2 * wg), (it + 1) & 1);
            if constexpr (t == SG_OUT) out_ready(LAST || it > 0);
            if constexpr (t == SG_SUM + 1 && !LAST) arrive(B_STG_EMPTY);
            if constexpr (t == (LAST ? 22 : SG_EPI)) mbar_wait(bars + 8 * (B_OUT_FREE + wg), (it & 1) ^ 1);
            constexpr bool g1seg = t % 6 >= 1 && t % 6 <= 3 && (!LAST || t < 18);
            if constexpr (t <= 25 || g1seg) {
                WG_FENCE();
                if constexpr (t <= 25) {
#pragma unroll
                    for (int j = (t == 5 ? 0 : t - 2); j <= t - 2; j++) gemm2_step(acc2, p[j], w2desc, j);
                }
                if constexpr (g1seg) {
                    if constexpr (t == 25) WG_COMMIT();
                    constexpr int c = (t / 6 + 1) % 4;
                    gemm1_step(h[c & 1], a, w1desc, c, (t % 6 - 1) * 2);
                    gemm1_step(h[c & 1], a, w1desc, c, (t % 6 - 1) * 2 + 1);
                }
                WG_COMMIT();
            }
            gelu_upto(Tc, std::integral_constant<int, (LAST ? 24 : 99)>{});
            if constexpr (t >= SG_EPI) {
#pragma unroll
                for (int i = 3 * (t - SG_EPI); i < 3 * (t - SG_EPI) + 3; i++) store_out(i);
            }
            if constexpr (!LAST) layernorm(Tc);
            SCHED_FENCE();
        };
#pragma unroll 1
        for (int it = 0; it < NT / 2 - 1; it++) {
            static_for<5, 29>([&](auto Tc) { segment(Tc, std::false_type{}, it); });
            wg_wait<0>();
        }
        {
            const uint32_t sb2 = __shfl_sync(0xffffffffu, lds32(bars + 8 * B_BASE), 0);
            w1desc = make_desc(sb2 + SM_W1, W1_LBO, W1_SBO);
            w2desc = make_desc(sb2 + SM_W2, W2_LBO, W2_SBO);
        }
        static_for<5, 26>([&](auto Tc) { segment(Tc, std::true_type{}, NT / 2 - 1); });
        wg_wait<0>();
        fence_regs(acc2);
#pragma unroll
        for (int i = 0; i < 6; i++) store_out(i);
        out_ready(true);
        TRS_(4);
    }
}

typedef CUresult (*PFN_encodeTiled)(CUtensorMap*, CUtensorMapDataType, cuuint32_t, void*, const cuuint64_t*,
                                    const cuuint64_t*, const cuuint32_t*, const cuuint32_t*, CUtensorMapInterleave,
                                    CUtensorMapSwizzle, CUtensorMapL2promotion, CUtensorMapFloatOOBfill);

}

extern "C" void kernel_launch(void* const* d_in, const int* in_sizes, int n_in, void* d_out, int out_size) {
    const __nv_bfloat16* x = (const __nv_bfloat16*)d_in[0];
    const __nv_bfloat16* dwl = (const __nv_bfloat16*)d_in[1];
    const __nv_bfloat16* dws = (const __nv_bfloat16*)d_in[2];
    const __nv_bfloat16* w1 = (const __nv_bfloat16*)d_in[3];
    const __nv_bfloat16* w2 = (const __nv_bfloat16*)d_in[4];

    static PFN_encodeTiled encode = nullptr;
    if (!encode) {
        void* fn = nullptr;
        cudaDriverEntryPointQueryResult qres;
        cudaGetDriverEntryPoint("cuTensorMapEncodeTiled", &fn, cudaEnableDefault, &qres);
        encode = (PFN_encodeTiled)fn;
        cudaFuncSetAttribute(fused_block_kernel, cudaFuncAttributeMaxDynamicSharedMemorySize, SMEM_TOTAL);
    }
    CUtensorMap rowmap, copymap, outmap;
    cuuint64_t gdim[3] = {(cuuint64_t)CH, (cuuint64_t)IMG_W, (cuuint64_t)IMG_H};
    cuuint64_t gstride[2] = {(cuuint64_t)PXB, (cuuint64_t)IMG_W * PXB};
    cuuint32_t estr[4] = {1, 1, 1, 1};
    cuuint32_t box_row[3] = {(cuuint32_t)CH, (cuuint32_t)ROW_PX, 2};
    cuuint32_t box_tile[3] = {(cuuint32_t)CH, (cuuint32_t)BW, (cuuint32_t)TR};
    encode(&rowmap, CU_TENSOR_MAP_DATA_TYPE_BFLOAT16, 3, (void*)x, gdim, gstride, box_row, estr,
           CU_TENSOR_MAP_INTERLEAVE_NONE, CU_TENSOR_MAP_SWIZZLE_NONE, CU_TENSOR_MAP_L2_PROMOTION_L2_256B,
           CU_TENSOR_MAP_FLOAT_OOB_FILL_NONE);
    cuuint64_t cdim[4] = {(cuuint64_t)CH, (cuuint64_t)BW, (cuuint64_t)(IMG_W / BW), (cuuint64_t)IMG_H};
    cuuint64_t cstride[3] = {(cuuint64_t)PXB, (cuuint64_t)BW * PXB, (cuuint64_t)IMG_W * PXB};
    cuuint32_t box_copy[4] = {(cuuint32_t)CH, (cuuint32_t)ROW_PX, 1, 2};
    encode(&copymap, CU_TENSOR_MAP_DATA_TYPE_BFLOAT16, 4, d_out, cdim, cstride, box_copy, estr,
           CU_TENSOR_MAP_INTERLEAVE_NONE, CU_TENSOR_MAP_SWIZZLE_NONE, CU_TENSOR_MAP_L2_PROMOTION_NONE,
           CU_TENSOR_MAP_FLOAT_OOB_FILL_NONE);
    encode(&outmap, CU_TENSOR_MAP_DATA_TYPE_BFLOAT16, 3, d_out, gdim, gstride, box_tile, estr,
           CU_TENSOR_MAP_INTERLEAVE_NONE, CU_TENSOR_MAP_SWIZZLE_NONE, CU_TENSOR_MAP_L2_PROMOTION_NONE,
           CU_TENSOR_MAP_FLOAT_OOB_FILL_NONE);
    fused_block_kernel<<<NCTA, NTHREADS, SMEM_TOTAL>>>(rowmap, copymap, outmap, dwl, dws, w1, w2);
}
```
